```python
import torch

def _softmax(x, axis=-1):
    return torch.softmax(x, dim=axis)
def _gelu(x):
    return torch.nn.functional.gelu(x, approximate="tanh")
def _silu(x):
    return torch.nn.functional.silu(x)
def _sigmoid(x):
    return torch.sigmoid(x)
def _layernorm(x, axis=-1, eps=1e-5):
    m = x.mean(dim=axis, keepdim=True)
    v = x.var(dim=axis, keepdim=True, unbiased=False)
    return (x - m) / torch.sqrt(v + eps)
def _scatter_add(tgt, idx, src, axis=0):
    return tgt.clone().index_add_(axis, idx, src)
def _segment_sum(src, seg, n):
    out = torch.zeros((n,) + src.shape[1:], dtype=src.dtype)
    return out.index_add_(0, seg, src)
def _pad(x, pw):
    flat = tuple(v for pair in reversed(pw) for v in pair)
    return torch.nn.functional.pad(x, flat)

kernel_name = 'sequential_preLN__spectral_fnet__geglu_ffn__prompt'

def setup_inputs():

    _w = (lambda a: (lambda t: t.to(torch.bfloat16) if t.is_floating_point() else t)(torch.as_tensor(a)))
    def _A_setup():
        B, S, D = 1, 2048, 640
        ns = torch.arange(S)[:, None] * torch.arange(S)[None, :]
        nd = torch.arange(D)[:, None] * torch.arange(D)[None, :]
        Ws_re = torch.cos(-2.0 * torch.pi * ns / S).to(float)
        Ws_im = torch.sin(-2.0 * torch.pi * ns / S).to(float)
        Wd_re = torch.cos(-2.0 * torch.pi * nd / D).to(float)
        Wd_im = torch.sin(-2.0 * torch.pi * nd / D).to(float)
        return {
            "x": _w((lambda *s: torch.randn(*s, dtype=torch.bfloat16) * 0.05)(B, S, D)),
            "dft_seq_re": _w(Ws_re),
            "dft_seq_im": _w(Ws_im),
            "dft_hid_re": _w(Wd_re),
            "dft_hid_im": _w(Wd_im),
        }
    _A_in = _A_setup()

    def _B_setup():
        B, S, D, F = 1, 2048, 640, 1728
        return {
            "x": _w((lambda *s: torch.randn(*s, dtype=torch.bfloat16) * 0.05)(B, S, D)),
            "w_gate": _w((lambda *s: torch.randn(*s, dtype=torch.bfloat16) * 0.2)(D, F)),
            "w_up": _w((lambda *s: torch.randn(*s, dtype=torch.bfloat16) * 0.2)(D, F)),
            "w_down": _w((lambda *s: torch.randn(*s, dtype=torch.bfloat16) * 0.2)(F, D)),
        }
    _B_in = _B_setup()

    return {
        "A_x": _A_in["x"],
        "A_dft_seq_re": _A_in["dft_seq_re"],
        "A_dft_seq_im": _A_in["dft_seq_im"],
        "A_dft_hid_re": _A_in["dft_hid_re"],
        "A_dft_hid_im": _A_in["dft_hid_im"],
        "B_x": _B_in["x"],
        "B_w_gate": _B_in["w_gate"],
        "B_w_up": _B_in["w_up"],
        "B_w_down": _B_in["w_down"],
    }

def reference(A_x, A_dft_seq_re, A_dft_seq_im, A_dft_hid_re, A_dft_hid_im, B_x, B_w_gate, B_w_up, B_w_down):
    def _A_ref(x, dft_seq_re, dft_seq_im, dft_hid_re, dft_hid_im):
        a = torch.einsum("bsd,ed->bse", x, dft_hid_re)
        b = torch.einsum("bsd,ed->bse", x, dft_hid_im)
        y = torch.einsum("ts,bse->bte", dft_seq_re, a) - torch.einsum("ts,bse->bte", dft_seq_im, b)
        return y

    def _B_ref(x, w_gate, w_up, w_down):
        return (_gelu(x @ w_gate) * (x @ w_up)) @ w_down

    x = A_x
    h = x + _A_ref(_layernorm(x, axis=-1), A_dft_seq_re, A_dft_seq_im, A_dft_hid_re, A_dft_hid_im)
    h2 = h + _B_ref(_layernorm(h, axis=-1), B_w_gate, B_w_up, B_w_down)
    return h2
```

```cpp
#include <cuda_runtime.h>
#include <cuda_bf16.h>
#include <cuda.h>
#include <stdint.h>

namespace {

constexpr int S_ = 2048, D_ = 640, F_ = 1728;
constexpr int NB = 7;
constexpr int BSLOT = 20480;
constexpr int NA = 10;
constexpr int R_BYTES = 81920;
constexpr int OFF_B = R_BYTES;
constexpr int OFF_CS = OFF_B + NB * BSLOT;
constexpr int OFF_LN = OFF_CS + 2 * 432 * 4;
constexpr int OFF_BAR = OFF_LN + 2 * 64 * 4;
constexpr int SMEM_BYTES = OFF_BAR + 512 + 1024;

constexpr int B_FULLB = 0, B_EMPTYB = 7, B_FULLA = 14, B_EMPTYA = 24, B_FULLA2 = 34, B_EMPTYA2 = 44,
              B_FULLH = 54  , B_HOWN = 58, B_G1A = 59, B_RFREE = 60, B_COUNT = 61;

constexpr int I_G1A = 0, I_G1B = 10, I_G2 = 20, I_S1Q = 84, I_S2Q = 89, I_S1R = 94, I_S2R = 109, I_S3 = 124,
              I_S4 = 144, I_G4 = 154;

constexpr uint32_t SPIN_LIMIT = 1u << 24;

__device__ __align__(1024) uint8_t g_ab[4 * 64 * 20480];
__device__ __align__(1024) uint8_t g_h[32 * 81920];
__device__ __align__(1024) uint8_t g_act[32 * 216 * 1024];
__device__ __align__(1024) uint8_t g_wd[4 * 216 * 2560];
__device__ __align__(128) float g_csum[8 * 3456];
__device__ __align__(128) float2 g_stats[32 * 4 * 64];
__device__ __align__(128) uint32_t g_flagA[4 * 32];
__device__ __align__(128) uint32_t g_flagB[4 * 32];
__device__ __align__(128) uint32_t g_flagH[32 * 32];
__device__ __align__(128) uint32_t g_flagAct[32 * 32];
__device__ __align__(128) uint32_t g_flagAux[32];
__device__ __align__(128) uint32_t g_epoch[160];
#define TSTAMP(i)
#define TSTAMP0(i)

__device__ __forceinline__ void mbar_init(uint32_t bar, uint32_t cnt) { asm volatile("mbarrier.init.shared::cta.b64 [%0], %1;" :: "r"(bar), "r"(cnt) : "memory"); }
__device__ __forceinline__ void mbar_expect_tx(uint32_t bar, uint32_t bytes) { asm volatile("mbarrier.arrive.expect_tx.shared::cta.b64 _, [%0], %1;" :: "r"(bar), "r"(bytes) : "memory"); }
__device__ __forceinline__ void mbar_arrive(uint32_t bar) { asm volatile("mbarrier.arrive.shared::cta.b64 _, [%0];" :: "r"(bar) : "memory"); }
__device__ __forceinline__ bool mbar_try(uint32_t bar, uint32_t parity) {
    uint32_t ok;
    asm volatile("{ .reg .pred p; mbarrier.try_wait.parity.shared::cta.b64 p, [%1], %2; selp.u32 %0, 1, 0, p; }" : "=r"(ok) : "r"(bar), "r"(parity) : "memory");
    return ok;
}
__device__ __forceinline__ void mbar_wait(uint32_t bar, uint32_t parity) {
    uint32_t it = 0;
    while (!mbar_try(bar, parity)) { if (++it > (1u << 20)) __trap(); }
}
__device__ __forceinline__ bool elect_one() { uint32_t p; asm volatile("{ .reg .pred P; elect.sync _|P, 0xffffffff; selp.u32 %0, 1, 0, P; }" : "=r"(p)); return p; }
__device__ __forceinline__ void tma2d(uint32_t dst, const CUtensorMap* m, int c0, int c1, uint32_t bar) {
    asm volatile("cp.async.bulk.tensor.2d.shared::cluster.global.mbarrier::complete_tx::bytes [%0], [%1, {%3, %4}], [%2];"
        :: "r"(dst), "l"(m), "r"(bar), "r"(c0), "r"(c1) : "memory");
}
__device__ __forceinline__ void tma3d(uint32_t dst, const CUtensorMap* m, int c0, int c1, int c2, uint32_t bar) {
    asm volatile("cp.async.bulk.tensor.3d.shared::cluster.global.mbarrier::complete_tx::bytes [%0], [%1, {%3, %4, %5}], [%2];"
        :: "r"(dst), "l"(m), "r"(bar), "r"(c0), "r"(c1), "r"(c2) : "memory");
}
__device__ __forceinline__ void bulk_ld(uint32_t dst, const void* src, uint32_t bytes, uint32_t bar) {
    asm volatile("cp.async.bulk.shared::cluster.global.mbarrier::complete_tx::bytes [%0], [%1], %2, [%3];"
        :: "r"(dst), "l"(src), "r"(bytes), "r"(bar) : "memory");
}
__device__ __forceinline__ void bulk_prefetch(const void* src, uint32_t bytes) {
    asm volatile("cp.async.bulk.prefetch.L2.global [%0], %1;" :: "l"(src), "r"(bytes) : "memory");
}
__device__ __forceinline__ void prefetch_tmap(const CUtensorMap* m) { asm volatile("prefetch.tensormap [%0];" :: "l"(m) : "memory"); }
__device__ __forceinline__ void fence_async_smem() { asm volatile("fence.proxy.async.shared::cta;" ::: "memory"); }
__device__ __forceinline__ void fence_async_global() { asm volatile("fence.proxy.async.global;" ::: "memory"); }
__device__ __forceinline__ uint32_t ld_acquire(const uint32_t* p) { uint32_t v; asm volatile("ld.acquire.gpu.global.u32 %0, [%1];" : "=r"(v) : "l"(p) : "memory"); return v; }
__device__ __forceinline__ void red_release(uint32_t* p) { asm volatile("red.release.gpu.global.add.u32 [%0], 1;" :: "l"(p) : "memory"); }
__device__ __forceinline__ void bar_sync(int id, int n) { asm volatile("bar.sync %0, %1;" :: "r"(id), "r"(n) : "memory"); }
__device__ __forceinline__ void bar_arrive(int id, int n) { asm volatile("bar.arrive %0, %1;" :: "r"(id), "r"(n) : "memory"); }
__device__ __forceinline__ void wg_fence() { asm volatile("wgmma.fence.sync.aligned;" ::: "memory"); }
__device__ __forceinline__ void wg_commit() { asm volatile("wgmma.commit_group.sync.aligned;" ::: "memory"); }
template <int N> __device__ __forceinline__ void wg_wait() { asm volatile("wgmma.wait_group.sync.aligned %0;" :: "n"(N) : "memory"); }
template <int N> __device__ __forceinline__ void fence_regs(float (&d)[N]) {
#pragma unroll
    for (int i = 0; i < N; i++) asm volatile("" : "+f"(d[i]) :: "memory");
}
__device__ __forceinline__ uint32_t pack_bf16(float lo, float hi) { uint32_t r; asm("cvt.rn.bf16x2.f32 %0, %1, %2;" : "=r"(r) : "f"(hi), "f"(lo)); return r; }
__device__ __forceinline__ float bf_lo(uint32_t w) { return __uint_as_float(w << 16); }
__device__ __forceinline__ float bf_hi(uint32_t w) { return __uint_as_float(w & 0xffff0000u); }
__device__ __forceinline__ uint4 ldg128(const void* p) { uint4 v; asm volatile("ld.global.nc.L1::no_allocate.v4.u32 {%0,%1,%2,%3}, [%4];" : "=r"(v.x), "=r"(v.y), "=r"(v.z), "=r"(v.w) : "l"(p)); return v; }
__device__ __forceinline__ uint32_t ldg32(const void* p) { uint32_t v; asm volatile("ld.global.nc.L1::no_allocate.u32 %0, [%1];" : "=r"(v) : "l"(p)); return v; }
__device__ __forceinline__ uint32_t ldcg32(const void* p) { uint32_t v; asm volatile("ld.global.cg.u32 %0, [%1];" : "=r"(v) : "l"(p) : "memory"); return v; }
__device__ __forceinline__ void stg32(void* p, uint32_t v) { asm volatile("st.global.u32 [%0], %1;" :: "l"(p), "r"(v) : "memory"); }
__device__ __forceinline__ void stg128(void* p, uint4 v) { asm volatile("st.global.v4.u32 [%0], {%1,%2,%3,%4};" :: "l"(p), "r"(v.x), "r"(v.y), "r"(v.z), "r"(v.w) : "memory"); }
__device__ __forceinline__ void sts128(uint32_t a, uint4 v) { asm volatile("st.shared.v4.u32 [%0], {%1,%2,%3,%4};" :: "r"(a), "r"(v.x), "r"(v.y), "r"(v.z), "r"(v.w) : "memory"); }
__device__ __forceinline__ uint4 lds128(uint32_t a) { uint4 v; asm volatile("ld.shared.v4.u32 {%0,%1,%2,%3}, [%4];" : "=r"(v.x), "=r"(v.y), "=r"(v.z), "=r"(v.w) : "r"(a) : "memory"); return v; }
__device__ __forceinline__ float2 lds64f(uint32_t a) { float2 v; asm volatile("ld.shared.v2.f32 {%0,%1}, [%2];" : "=f"(v.x), "=f"(v.y) : "r"(a) : "memory"); return v; }
__device__ __forceinline__ float lds32f(uint32_t a) { float v; asm volatile("ld.shared.f32 %0, [%1];" : "=f"(v) : "r"(a) : "memory"); return v; }
__device__ __forceinline__ void sts32f(uint32_t a, float v) { asm volatile("st.shared.f32 [%0], %1;" :: "r"(a), "f"(v) : "memory"); }
__device__ __forceinline__ void stsm4(uint32_t a, uint32_t r0, uint32_t r1, uint32_t r2, uint32_t r3) {
    asm volatile("stmatrix.sync.aligned.m8n8.x4.shared.b16 [%0], {%1,%2,%3,%4};" :: "r"(a), "r"(r0), "r"(r1), "r"(r2), "r"(r3) : "memory");
}
__device__ __forceinline__ void ldsm4(uint32_t a, uint32_t& r0, uint32_t& r1, uint32_t& r2, uint32_t& r3) {
    asm volatile("ldmatrix.sync.aligned.m8n8.x4.shared.b16 {%0,%1,%2,%3}, [%4];" : "=r"(r0), "=r"(r1), "=r"(r2), "=r"(r3) : "r"(a) : "memory");
}
__device__ __forceinline__ void mma_rowsum(float (&c)[4], const uint4& a) {
    asm volatile("mma.sync.aligned.m16n8k16.row.col.f32.bf16.bf16.f32 {%0,%1,%2,%3}, {%4,%5,%6,%7}, {%8,%8}, {%0,%1,%2,%3};"
        : "+f"(c[0]), "+f"(c[1]), "+f"(c[2]), "+f"(c[3]) : "r"(a.x), "r"(a.y), "r"(a.z), "r"(a.w), "r"(0x3F803F80u));
}
__device__ __forceinline__ uint32_t sub_bf16x2(uint32_t a, uint32_t b) { uint32_t r; asm("sub.rn.bf16x2 %0, %1, %2;" : "=r"(r) : "r"(a), "r"(b)); return r; }

template <int TB>
__device__ __forceinline__ void wgmma_n160(float (&d)[80], uint64_t da, uint64_t db, int scaleD) {
    asm volatile("{ .reg .pred p; setp.ne.b32 p, %82, 0;\n"
        "wgmma.mma_async.sync.aligned.m64n160k16.f32.bf16.bf16 {%0,%1,%2,%3,%4,%5,%6,%7,%8,%9,%10,%11,%12,%13,%14,%15,%16,%17,%18,%19,%20,%21,%22,%23,%24,%25,%26,%27,%28,%29,%30,%31,%32,%33,%34,%35,%36,%37,%38,%39,%40,%41,%42,%43,%44,%45,%46,%47,%48,%49,%50,%51,%52,%53,%54,%55,%56,%57,%58,%59,%60,%61,%62,%63,%64,%65,%66,%67,%68,%69,%70,%71,%72,%73,%74,%75,%76,%77,%78,%79}, %80, %81, p, 1, 1, 0, %83; }"
        : "+f"(d[0]), "+f"(d[1]), "+f"(d[2]), "+f"(d[3]), "+f"(d[4]), "+f"(d[5]), "+f"(d[6]), "+f"(d[7]), "+f"(d[8]), "+f"(d[9]), "+f"(d[10]), "+f"(d[11]),
        "+f"(d[12]), "+f"(d[13]), "+f"(d[14]), "+f"(d[15]), "+f"(d[16]), "+f"(d[17]), "+f"(d[18]), "+f"(d[19]), "+f"(d[20]), "+f"(d[21]), "+f"(d[22]),
        "+f"(d[23]), "+f"(d[24]), "+f"(d[25]), "+f"(d[26]), "+f"(d[27]), "+f"(d[28]), "+f"(d[29]), "+f"(d[30]), "+f"(d[31]), "+f"(d[32]), "+f"(d[33]),
        "+f"(d[34]), "+f"(d[35]), "+f"(d[36]), "+f"(d[37]), "+f"(d[38]), "+f"(d[39]), "+f"(d[40]), "+f"(d[41]), "+f"(d[42]), "+f"(d[43]), "+f"(d[44]),
        "+f"(d[45]), "+f"(d[46]), "+f"(d[47]), "+f"(d[48]), "+f"(d[49]), "+f"(d[50]), "+f"(d[51]), "+f"(d[52]), "+f"(d[53]), "+f"(d[54]), "+f"(d[55]),
        "+f"(d[56]), "+f"(d[57]), "+f"(d[58]), "+f"(d[59]), "+f"(d[60]), "+f"(d[61]), "+f"(d[62]), "+f"(d[63]), "+f"(d[64]), "+f"(d[65]), "+f"(d[66]),
        "+f"(d[67]), "+f"(d[68]), "+f"(d[69]), "+f"(d[70]), "+f"(d[71]), "+f"(d[72]), "+f"(d[73]), "+f"(d[74]), "+f"(d[75]), "+f"(d[76]), "+f"(d[77]),
        "+f"(d[78]), "+f"(d[79])
        : "l"(da), "l"(db), "r"(scaleD), "n"(TB));
}
template <int TB>
__device__ __forceinline__ void wgmma_n256(float (&d)[128], uint64_t da, uint64_t db, int scaleD) {
    asm volatile("{ .reg .pred p; setp.ne.b32 p, %130, 0;\n"
        "wgmma.mma_async.sync.aligned.m64n256k16.f32.bf16.bf16 {%0,%1,%2,%3,%4,%5,%6,%7,%8,%9,%10,%11,%12,%13,%14,%15,%16,%17,%18,%19,%20,%21,%22,%23,%24,%25,%26,%27,%28,%29,%30,%31,%32,%33,%34,%35,%36,%37,%38,%39,%40,%41,%42,%43,%44,%45,%46,%47,%48,%49,%50,%51,%52,%53,%54,%55,%56,%57,%58,%59,%60,%61,%62,%63,%64,%65,%66,%67,%68,%69,%70,%71,%72,%73,%74,%75,%76,%77,%78,%79,%80,%81,%82,%83,%84,%85,%86,%87,%88,%89,%90,%91,%92,%93,%94,%95,%96,%97,%98,%99,%100,%101,%102,%103,%104,%105,%106,%107,%108,%109,%110,%111,%112,%113,%114,%115,%116,%117,%118,%119,%120,%121,%122,%123,%124,%125,%126,%127}, %128, %129, p, 1, 1, 0, %131; }"
        : "+f"(d[0]), "+f"(d[1]), "+f"(d[2]), "+f"(d[3]), "+f"(d[4]), "+f"(d[5]), "+f"(d[6]), "+f"(d[7]), "+f"(d[8]), "+f"(d[9]), "+f"(d[10]), "+f"(d[11]),
        "+f"(d[12]), "+f"(d[13]), "+f"(d[14]), "+f"(d[15]), "+f"(d[16]), "+f"(d[17]), "+f"(d[18]), "+f"(d[19]), "+f"(d[20]), "+f"(d[21]), "+f"(d[22]),
        "+f"(d[23]), "+f"(d[24]), "+f"(d[25]), "+f"(d[26]), "+f"(d[27]), "+f"(d[28]), "+f"(d[29]), "+f"(d[30]), "+f"(d[31]), "+f"(d[32]), "+f"(d[33]),
        "+f"(d[34]), "+f"(d[35]), "+f"(d[36]), "+f"(d[37]), "+f"(d[38]), "+f"(d[39]), "+f"(d[40]), "+f"(d[41]), "+f"(d[42]), "+f"(d[43]), "+f"(d[44]),
        "+f"(d[45]), "+f"(d[46]), "+f"(d[47]), "+f"(d[48]), "+f"(d[49]), "+f"(d[50]), "+f"(d[51]), "+f"(d[52]), "+f"(d[53]), "+f"(d[54]), "+f"(d[55]),
        "+f"(d[56]), "+f"(d[57]), "+f"(d[58]), "+f"(d[59]), "+f"(d[60]), "+f"(d[61]), "+f"(d[62]), "+f"(d[63]), "+f"(d[64]), "+f"(d[65]), "+f"(d[66]),
        "+f"(d[67]), "+f"(d[68]), "+f"(d[69]), "+f"(d[70]), "+f"(d[71]), "+f"(d[72]), "+f"(d[73]), "+f"(d[74]), "+f"(d[75]), "+f"(d[76]), "+f"(d[77]),
        "+f"(d[78]), "+f"(d[79]), "+f"(d[80]), "+f"(d[81]), "+f"(d[82]), "+f"(d[83]), "+f"(d[84]), "+f"(d[85]), "+f"(d[86]), "+f"(d[87]), "+f"(d[88]),
        "+f"(d[89]), "+f"(d[90]), "+f"(d[91]), "+f"(d[92]), "+f"(d[93]), "+f"(d[94]), "+f"(d[95]), "+f"(d[96]), "+f"(d[97]), "+f"(d[98]), "+f"(d[99]),
        "+f"(d[100]), "+f"(d[101]), "+f"(d[102]), "+f"(d[103]), "+f"(d[104]), "+f"(d[105]), "+f"(d[106]), "+f"(d[107]), "+f"(d[108]), "+f"(d[109]),
        "+f"(d[110]), "+f"(d[111]), "+f"(d[112]), "+f"(d[113]), "+f"(d[114]), "+f"(d[115]), "+f"(d[116]), "+f"(d[117]), "+f"(d[118]), "+f"(d[119]),
        "+f"(d[120]), "+f"(d[121]), "+f"(d[122]), "+f"(d[123]), "+f"(d[124]), "+f"(d[125]), "+f"(d[126]), "+f"(d[127])
        : "l"(da), "l"(db), "r"(scaleD), "n"(TB));
}
template <int TB>
__device__ __forceinline__ void wgmma_n112(float (&d)[56], uint64_t da, uint64_t db, int scaleD) {
    asm volatile("{ .reg .pred p; setp.ne.b32 p, %58, 0;\n"
        "wgmma.mma_async.sync.aligned.m64n112k16.f32.bf16.bf16 {%0,%1,%2,%3,%4,%5,%6,%7,%8,%9,%10,%11,%12,%13,%14,%15,%16,%17,%18,%19,%20,%21,%22,%23,%24,%25,%26,%27,%28,%29,%30,%31,%32,%33,%34,%35,%36,%37,%38,%39,%40,%41,%42,%43,%44,%45,%46,%47,%48,%49,%50,%51,%52,%53,%54,%55}, %56, %57, p, 1, 1, 0, %59; }"
        : "+f"(d[0]), "+f"(d[1]), "+f"(d[2]), "+f"(d[3]), "+f"(d[4]), "+f"(d[5]), "+f"(d[6]), "+f"(d[7]), "+f"(d[8]), "+f"(d[9]), "+f"(d[10]), "+f"(d[11]),
        "+f"(d[12]), "+f"(d[13]), "+f"(d[14]), "+f"(d[15]), "+f"(d[16]), "+f"(d[17]), "+f"(d[18]), "+f"(d[19]), "+f"(d[20]), "+f"(d[21]), "+f"(d[22]),
        "+f"(d[23]), "+f"(d[24]), "+f"(d[25]), "+f"(d[26]), "+f"(d[27]), "+f"(d[28]), "+f"(d[29]), "+f"(d[30]), "+f"(d[31]), "+f"(d[32]), "+f"(d[33]),
        "+f"(d[34]), "+f"(d[35]), "+f"(d[36]), "+f"(d[37]), "+f"(d[38]), "+f"(d[39]), "+f"(d[40]), "+f"(d[41]), "+f"(d[42]), "+f"(d[43]), "+f"(d[44]),
        "+f"(d[45]), "+f"(d[46]), "+f"(d[47]), "+f"(d[48]), "+f"(d[49]), "+f"(d[50]), "+f"(d[51]), "+f"(d[52]), "+f"(d[53]), "+f"(d[54]), "+f"(d[55])
        : "l"(da), "l"(db), "r"(scaleD), "n"(TB));
}

constexpr uint64_t desc_hi(uint32_t lbo, uint32_t sbo, uint32_t mode) {
    return ((uint64_t)(lbo >> 4) << 16) | ((uint64_t)(sbo >> 4) << 32) | ((uint64_t)mode << 62);
}
constexpr uint64_t DH_SW128_K = desc_hi(16, 1024, 1);
constexpr uint64_t DH_BLK_A = desc_hi(1024, 128, 0);
constexpr uint64_t DH_BLK_B = desc_hi(2560, 128, 0);
constexpr uint64_t DH_W32 = desc_hi(4096, 1024, 1);
constexpr uint64_t DH_W64 = desc_hi(8192, 1024, 1);

struct Ring {
    uint32_t s, ph;
    __device__ __forceinline__ Ring(int idx, int n) : s(idx % n), ph((idx / n) & 1) {}
    template <int N> __device__ __forceinline__ void next() { if (++s == N) { s = 0; ph ^= 1; } }
};

__device__ __forceinline__ int g4_atom(int c) { return c < 24 ? ((c & 7) >> 1) * 6 + (c >> 3) * 2 + (c & 1) : c; }

struct Params {
    CUtensorMap wdre, wdim, wsre, wsim, wg, wu, wg2, wu2;
    const __nv_bfloat16 *x, *ws_re, *ws_im, *w_gate, *w_up, *w_down;
    __nv_bfloat16* out;
};

__device__ __forceinline__ float geglu(float g, float u) {
    const float c0 = -2.0f * 0.7978845608028654f * 1.4426950408889634f, c1 = c0 * 0.044715f;
    float t = g * fmaf(g * g, c1, c0);
    float e; asm("ex2.approx.ftz.f32 %0, %1;" : "=f"(e) : "f"(t));
    float r; asm("rcp.approx.ftz.f32 %0, %1;" : "=f"(r) : "f"(e + 1.0f));
    return (g * u) * r;
}

__device__ __forceinline__ void g3_run(float (&acc)[128], uint32_t sR, uint32_t sB, uint32_t bars, int idx0, int j, int i0, int i1,
                                       bool first, bool waitH, int hand_id, bool lead) {
    Ring rb(idx0, NB);
    int prev = -1;
    for (int i = i0; i < i1; i++) {
        if (waitH && i > 0) mbar_wait(bars + 8 * (B_FULLH + i), 0);
        uint32_t a0 = sR + (j ^ i) * 20480;
#pragma unroll 1
        for (int kk = 0; kk < 5; kk++) {
            mbar_wait(bars + 8 * (B_FULLB + rb.s), rb.ph);
            uint64_t da = DH_BLK_A | (uint64_t)((a0 + kk * 4096) >> 4), db = DH_W32 | (uint64_t)((sB + rb.s * BSLOT) >> 4);
            wg_fence();
            wgmma_n256<1>(acc, da, db, first ? 0 : 1);
            wgmma_n256<1>(acc, da + 128, db + 128, 1);
            wg_commit();
            first = false;
            if (i == i1 - 1 && kk == 4) bar_arrive(hand_id, 256);
            wg_wait<1>();
            if (prev >= 0 && lead) mbar_arrive(bars + 8 * (B_EMPTYB + prev));
            prev = rb.s;
            rb.next<NB>();
        }
    }
    wg_wait<0>();
    if (lead) mbar_arrive(bars + 8 * (B_EMPTYB + prev));
    fence_regs(acc);
}

struct RowStat { float mean_lo, rstd_lo, mean_hi, rstd_hi; };

__device__ __forceinline__ RowStat load_stats(int g, int w, int lane, uint32_t target) {
    uint32_t it = 0;
    while (true) {
        uint32_t v = lane < 4 ? ld_acquire(&g_flagH[g * 32 + lane]) : target;
        if (__all_sync(0xffffffffu, v == target)) break;
        if (++it > SPIN_LIMIT) __trap();
    }
    __syncwarp();
    RowStat r;
#pragma unroll
    for (int hi = 0; hi < 2; hi++) {
        int row = 16 * w + (lane >> 2) + 8 * hi;
        float2 p = __ldcg(&g_stats[(g * 4 + (lane & 3)) * 64 + row]);
        float m = p.x;
        m += __shfl_xor_sync(0xffffffffu, m, 1); m += __shfl_xor_sync(0xffffffffu, m, 2);
        m *= 0.25f;
        float d = p.x - m;
        float m2 = fmaf(160.0f * d, d, p.y);
        m2 += __shfl_xor_sync(0xffffffffu, m2, 1); m2 += __shfl_xor_sync(0xffffffffu, m2, 2);
        float rs = rsqrtf(m2 * (1.0f / 640.0f) + 1e-5f);
        if (hi == 0) { r.mean_lo = m; r.rstd_lo = rs; } else { r.mean_hi = m; r.rstd_hi = rs; }
    }
    return r;
}

template <int T0, int NT, int UOFF, int NACC>
__device__ __forceinline__ void g3_epilogue(const float (&acc)[NACC], const RowStat& st, uint32_t sCS, int col0, uint8_t* dst, int lane) {
    uint32_t cg = sCS + (col0 + 2 * (lane & 3)) * 4, cu = cg + 432 * 4;
#pragma unroll
    for (int t = T0; t < NT; t++) {
        float2 sg = lds64f(cg + t * 32), su = lds64f(cu + t * 32);
        float g0 = fmaf(-st.mean_lo, sg.x, acc[4 * t + 0]) * st.rstd_lo, g1 = fmaf(-st.mean_lo, sg.y, acc[4 * t + 1]) * st.rstd_lo;
        float g2 = fmaf(-st.mean_hi, sg.x, acc[4 * t + 2]) * st.rstd_hi, g3 = fmaf(-st.mean_hi, sg.y, acc[4 * t + 3]) * st.rstd_hi;
        float u0 = fmaf(-st.mean_lo, su.x, acc[UOFF + 4 * t + 0]) * st.rstd_lo, u1 = fmaf(-st.mean_lo, su.y, acc[UOFF + 4 * t + 1]) * st.rstd_lo;
        float u2 = fmaf(-st.mean_hi, su.x, acc[UOFF + 4 * t + 2]) * st.rstd_hi, u3 = fmaf(-st.mean_hi, su.y, acc[UOFF + 4 * t + 3]) * st.rstd_hi;
        stg32(dst + t * 1024, pack_bf16(geglu(g0, u0), geglu(g1, u1)));
        stg32(dst + t * 1024 + 128, pack_bf16(geglu(g2, u2), geglu(g3, u3)));
    }
}

__device__ __forceinline__ void publish(uint32_t* flag, int lane) {
    __syncwarp();
    if (lane == 0) red_release(flag);
}

__device__ __forceinline__ void g1_run(float (&acc)[80], uint32_t sR, uint32_t sB, uint32_t bars, int idx0, int hand_id, bool lead, bool relA) {
    Ring rb(idx0, NB);
    int prev = -1;
#pragma unroll 1
    for (int c = 0; c < 10; c++) {
        mbar_wait(bars + 8 * (B_FULLB + rb.s), rb.ph);
        uint64_t da = DH_SW128_K | (uint64_t)((sR + c * 8192) >> 4), db = DH_SW128_K | (uint64_t)((sB + rb.s * BSLOT) >> 4);
        wg_fence();
        wgmma_n160<0>(acc, da, db, c > 0);
        wgmma_n160<0>(acc, da + 2, db + 2, 1);
        wgmma_n160<0>(acc, da + 4, db + 4, 1);
        wgmma_n160<0>(acc, da + 6, db + 6, 1);
        wg_commit();
        if (c == 9) bar_arrive(hand_id, 256);
        wg_wait<1>();
        if (prev >= 0 && lead) { mbar_arrive(bars + 8 * (B_EMPTYB + prev)); if (relA) mbar_arrive(bars + 8 * (B_EMPTYA + c - 1)); }
        prev = rb.s;
        rb.next<NB>();
    }
    wg_wait<0>();
    if (lead) { mbar_arrive(bars + 8 * (B_EMPTYB + prev)); if (relA) mbar_arrive(bars + 8 * (B_EMPTYA + 9)); else mbar_arrive(bars + 8 * B_G1A); }
    fence_regs(acc);
}

__device__ __forceinline__ void g1_epilogue(const float (&acc)[80], float s_lo, float s_hi, uint8_t* dst) {
#pragma unroll
    for (int t = 0; t < 20; t++) {
        stg32(dst + t * 128, pack_bf16(acc[4 * t] * s_lo, acc[4 * t + 1] * s_lo));
        stg32(dst + 2560 + t * 128, pack_bf16(acc[4 * t + 2] * s_hi, acc[4 * t + 3] * s_hi));
    }
}

template <int NCH, bool A_SW128>
__device__ __forceinline__ void stream_run(float (&acc)[80], uint32_t sR, uint32_t sB, uint32_t bars, int idx0, int fullA, int emptyA, bool lead) {
    Ring rb(idx0, NB), ra(0, NA);
    int pb = -1, pa = -1;
#pragma unroll 1
    for (int c = 0; c < NCH; c++) {
        mbar_wait(bars + 8 * (fullA + ra.s), ra.ph);
        mbar_wait(bars + 8 * (B_FULLB + rb.s), rb.ph);
        uint64_t da = (A_SW128 ? DH_SW128_K : DH_BLK_A) | (uint64_t)((sR + ra.s * 8192) >> 4), db = DH_BLK_B | (uint64_t)((sB + rb.s * BSLOT) >> 4);
        constexpr int AS = A_SW128 ? 2 : 128;
        wg_fence();
        wgmma_n160<1>(acc, da, db, 1);
        wgmma_n160<1>(acc, da + AS, db + 320, 1);
        wgmma_n160<1>(acc, da + 2 * AS, db + 640, 1);
        wgmma_n160<1>(acc, da + 3 * AS, db + 960, 1);
        wg_commit();
        wg_wait<1>();
        if (pb >= 0 && lead) { mbar_arrive(bars + 8 * (B_EMPTYB + pb)); mbar_arrive(bars + 8 * (emptyA + pa)); }
        pb = rb.s; pa = ra.s;
        rb.next<NB>(); ra.next<NA>();
    }
    wg_wait<0>();
    if (lead) mbar_arrive(bars + 8 * (B_EMPTYB + pb));
    fence_regs(acc);
}

constexpr int BAR_LN = 1, BAR_TO1 = 2, BAR_TO0 = 3, BAR_WG0 = 4, BAR_WG1 = 5, BAR_RSTD = 6;

__global__ void __launch_bounds__(384, 1) fused_kernel(const __grid_constant__ Params P) {
    extern __shared__ __align__(1024) uint8_t smem_raw[];
    uint32_t sraw;
    asm volatile("{ .reg .u64 t; cvta.to.shared.u64 t, %1; cvt.u32.u64 %0, t; }" : "=r"(sraw) : "l"(smem_raw));
    const uint32_t sR = (sraw + 1023) & ~1023u, sB = sR + OFF_B, sCS = sR + OFF_CS, sLN = sR + OFF_LN, bars = sR + OFF_BAR;
    const int warp = __shfl_sync(0xffffffffu, (int)(threadIdx.x >> 5), 0), lane = threadIdx.x & 31;

    int slot;
    {
        uint32_t smid, nsmid;
        asm volatile("mov.u32 %0, %%smid;" : "=r"(smid));
        asm volatile("mov.u32 %0, %%nsmid;" : "=r"(nsmid));
        if (nsmid == 132 && gridDim.x == 132) {
            if (smid < 64) { int gp = (smid & 15) >> 1, pos = (smid >> 4) * 2 + (smid & 1); slot = gp ? (gp - 1) * 16 + pos : 112 + pos; }
            else if (smid < 120) { int t = smid - 64, r = t / 14, q = t - r * 14; slot = (q >> 1) * 16 + 8 + r * 2 + (q & 1); }
            else slot = smid;
        } else slot = blockIdx.x;
        slot = __shfl_sync(0xffffffffu, slot, 0);
    }
    if (slot >= 128) {
        if (threadIdx.x == 0) {
            const uint32_t epoch = __ldcg(&g_epoch[slot]) + 1;
            uint32_t it = 0;
            while (ld_acquire(&g_flagAux[0]) != epoch * 512u) { __nanosleep(500); if (++it > (1u << 21)) __trap(); }
            g_epoch[slot] = epoch;
        }
        return;
    }
    const int g = slot >> 2, j = slot & 3;
    TSTAMP0(warp >> 2);

    if (warp >= 8) {
        asm volatile("setmaxnreg.dec.sync.aligned.u32 40;");
        if (warp == 9) {
            if (lane == 0) {
                for (int i = 0; i < B_COUNT; i++) mbar_init(bars + 8 * i, i == B_HOWN ? 128 : 1);
                asm volatile("fence.mbarrier_init.release.cluster;" ::: "memory");
                fence_async_smem();
            }
            __syncwarp();
            if (elect_one()) {
                for (int c = 0; c < NB; c++) {
                    mbar_expect_tx(bars + 8 * (B_FULLB + c), 20480);
                    tma2d(sB + c * BSLOT, &P.wdre, c * 64, j * 160, bars + 8 * (B_FULLB + c));
                }
            }
            __syncwarp();
        }
        bar_sync(0, 384);
        const uint32_t epoch = __ldcg(&g_epoch[slot]) + 1;
        if (warp == 9) {
            Ring rb(NB, NB);
            auto acquire = [&]() { mbar_wait(bars + 8 * (B_EMPTYB + rb.s), rb.ph ^ 1); };
            if (lane == 0) { prefetch_tmap(&P.wdim); prefetch_tmap(&P.wg); prefetch_tmap(&P.wu); prefetch_tmap(&P.wg2); prefetch_tmap(&P.wu2); }
#pragma unroll 1
            for (int c = NB; c < 20; c++) {
                acquire();
                if (elect_one()) {
                    mbar_expect_tx(bars + 8 * (B_FULLB + rb.s), 20480);
                    tma2d(sB + rb.s * BSLOT, c < 10 ? &P.wdre : &P.wdim, (c < 10 ? c : c - 10) * 64, j * 160, bars + 8 * (B_FULLB + rb.s));
                }
                __syncwarp();
                rb.next<NB>();
            }
            TSTAMP(40);
            const uint32_t tgt4 = epoch * 4u;
#pragma unroll 1
            for (int half = 0; half < 2; half++) {
                const uint32_t* fl = (half ? g_flagB : g_flagA) + j * 32 + lane;
                uint32_t ready = 0;
#pragma unroll 1
                for (int c = 0; c < 32; c++) {
                    if (!((ready >> c) & 1)) {
                        uint32_t it = 0;
                        do { ready = __ballot_sync(0xffffffffu, ld_acquire(fl) == tgt4); if (++it > SPIN_LIMIT) __trap(); } while (!((ready >> c) & 1));
                        __syncwarp();
                        fence_async_global();
                    }
                    if (c == 0) { TSTAMP(41 + half); }
                    acquire();
                    if (elect_one()) {
                        mbar_expect_tx(bars + 8 * (B_FULLB + rb.s), 20480);
                        bulk_ld(sB + rb.s * BSLOT, g_ab + (size_t)(j * 64 + half * 32 + c) * 20480, 20480, bars + 8 * (B_FULLB + rb.s));
                    }
                    __syncwarp();
                    rb.next<NB>();
                }
            }
#pragma unroll 1
            for (int seg = 0; seg < 5; seg++) {
                const int sub = seg == 4 ? 2 : (seg & 1), i0 = (seg == 2 || seg == 3) ? 1 : 0, i1 = seg < 2 ? 1 : 4;
                const int atom = j * 6 + sub * 2;
#pragma unroll 1
                for (int i = i0; i < i1; i++)
#pragma unroll 1
                    for (int kk = 0; kk < 5; kk++) {
                        acquire();
                        if (elect_one()) {
                            const int k0 = (j ^ i) * 160 + kk * 32;
                            mbar_expect_tx(bars + 8 * (B_FULLB + rb.s), 16384);
                            tma3d(sB + rb.s * BSLOT, &P.wg, 0, k0, atom, bars + 8 * (B_FULLB + rb.s));
                            tma3d(sB + rb.s * BSLOT + 8192, &P.wu, 0, k0, atom, bars + 8 * (B_FULLB + rb.s));
                        }
                        __syncwarp();
                        rb.next<NB>();
                    }
            }
#pragma unroll 1
            for (int c = 0; c < 10; c++) {
                acquire();
                if (elect_one()) {
                    mbar_expect_tx(bars + 8 * (B_FULLB + rb.s), 16384);
                    tma2d(sB + rb.s * BSLOT, &P.wg2, 1536 + 48 * j, c * 64, bars + 8 * (B_FULLB + rb.s));
                    tma2d(sB + rb.s * BSLOT + 8192, &P.wu2, 1536 + 48 * j, c * 64, bars + 8 * (B_FULLB + rb.s));
                }
                __syncwarp();
                rb.next<NB>();
            }
            {
                uint32_t it = 0;
                while (ld_acquire(&g_flagAux[0]) != epoch * 512u) { if (++it > SPIN_LIMIT) __trap(); }
                fence_async_global();
            }
#pragma unroll 1
            for (int c = 0; c < 27; c++) {
                acquire();
                if (elect_one()) {
                    mbar_expect_tx(bars + 8 * (B_FULLB + rb.s), 20480);
                    bulk_ld(sB + rb.s * BSLOT, g_wd + (size_t)(j * 27 + g4_atom(c)) * 20480, 20480, bars + 8 * (B_FULLB + rb.s));
                }
                __syncwarp();
                rb.next<NB>();
            }
        } else if (warp == 8) {
            if (lane == 0) { prefetch_tmap(&P.wsre); prefetch_tmap(&P.wsim); }
            mbar_wait(bars + 8 * (B_FULLB + 5), 0);
            if (lane < 16) bulk_prefetch(P.ws_re + (size_t)(g * 64 + j * 16 + lane) * S_, 4096);
            mbar_wait(bars + 8 * B_G1A, 0);
            Ring ra(0, NA);
#pragma unroll 1
            for (int c = 0; c < 64; c++) {
                mbar_wait(bars + 8 * (B_EMPTYA + ra.s), ra.ph);
                if (elect_one()) {
                    mbar_expect_tx(bars + 8 * (B_FULLA + ra.s), 8192);
                    tma2d(sR + ra.s * 8192, c < 32 ? &P.wsre : &P.wsim, (c & 31) * 64, g * 64, bars + 8 * (B_FULLA + ra.s));
                }
                __syncwarp();
                if (c == 9 && lane < 16) bulk_prefetch(P.ws_im + (size_t)(g * 64 + j * 16 + lane) * S_, 4096);
                ra.next<NA>();
            }
            const uint32_t tgt4 = epoch * 4u;
            mbar_wait(bars + 8 * B_HOWN, 0);
            {
                bool done = !(lane >= 1 && lane <= 3);
                uint32_t it = 0;
                while (true) {
                    if (!done && ld_acquire(&g_flagH[g * 32 + (j ^ lane)]) == tgt4) {
                        fence_async_global();
                        mbar_expect_tx(bars + 8 * (B_FULLH + lane), 20480);
                        bulk_ld(sR + (j ^ lane) * 20480, g_h + (size_t)g * 81920 + (j ^ lane) * 20480, 20480, bars + 8 * (B_FULLH + lane));
                        done = true;
                    }
                    if (__all_sync(0xffffffffu, done)) break;
                    if (++it > SPIN_LIMIT) __trap();
                }
            }
            TSTAMP(44);
            mbar_wait(bars + 8 * B_RFREE, 0);
            Ring r2(0, NA);
            uint32_t ready = 0;
#pragma unroll 1
            for (int c = 0; c < 27; c++) {
                const uint32_t need = c < 24 ? (1u << ((c >> 3) * 4 + ((c & 7) >> 1))) : 0xF000u;
                if ((ready & need) != need) {
                    uint32_t it = 0;
                    do { ready = __ballot_sync(0xffffffffu, lane < 16 && ld_acquire(&g_flagAct[g * 32 + (lane & 15)]) == tgt4); if (++it > SPIN_LIMIT) __trap(); } while ((ready & need) != need);
                    __syncwarp();
                    fence_async_global();
                }
                mbar_wait(bars + 8 * (B_EMPTYA2 + r2.s), r2.ph);
                if (elect_one()) {
                    mbar_expect_tx(bars + 8 * (B_FULLA2 + r2.s), 8192);
                    bulk_ld(sR + r2.s * 8192, g_act + (size_t)(g * 27 + g4_atom(c)) * 8192, 8192, bars + 8 * (B_FULLA2 + r2.s));
                }
                __syncwarp();
                r2.next<NA>();
            }
        }
    } else {
        asm volatile("setmaxnreg.inc.sync.aligned.u32 232;");
        const int w = warp & 3;
        const bool lead = (threadIdx.x & 127) == 0;
        uint32_t epoch;
        {
            uint4 xv[20];
            const __nv_bfloat16* xp = P.x + (size_t)(g * 64 + warp * 8 + (lane >> 2)) * D_ + (lane & 3) * 8;
#pragma unroll
            for (int i = 0; i < 20; i++) xv[i] = ldg128(xp + ((i ^ ((lane >> 2) & 1)) * 32));
            asm volatile("ld.global.cg.u32 %0, [%1];" : "=r"(epoch) : "l"(&g_epoch[slot]));
            bar_sync(0, 384);
            float c0[4] = {0, 0, 0, 0}, c1[4] = {0, 0, 0, 0};
#pragma unroll
            for (int i = 0; i < 20; i += 2) { mma_rowsum(c0, xv[i]); mma_rowsum(c1, xv[i + 1]); }
            const float mean = ((c0[0] + c0[2]) + (c1[0] + c1[2])) * (1.0f / 640.0f);
            const uint32_t mb = pack_bf16(mean, mean);
            const int r = lane >> 2, row = warp * 8 + r;
            const uint32_t base = sR + row * 128;
#pragma unroll
            for (int i = 0; i < 20; i++) {
                uint4 v = xv[i];
                v.x = sub_bf16x2(v.x, mb); v.y = sub_bf16x2(v.y, mb); v.z = sub_bf16x2(v.z, mb); v.w = sub_bf16x2(v.w, mb);
                const int u = (((i ^ r) & 1) * 4 + (lane & 3)) ^ r;
                sts128(base + (i >> 1) * 8192 + u * 16, v);
            }
            if ((lane & 3) == 0) sts32f(sLN + row * 4, mean - bf_lo(mb));
            fence_async_smem();
            bar_sync(BAR_LN, 256);
        }
        TSTAMP0(3 + (warp >> 2));
        epoch += 1;
        const uint32_t tgt4 = epoch * 4u;
        if (warp < 4) {
            {
                float acc[80];
                g1_run(acc, sR, sB, bars, I_G1A, BAR_TO1, lead, false);
                TSTAMP0(5);
                bar_sync(BAR_RSTD, 256);
                const float s_lo = lds32f(sLN + 256 + (16 * w + (lane >> 2)) * 4), s_hi = lds32f(sLN + 256 + (16 * w + 8 + (lane >> 2)) * 4);
                g1_epilogue(acc, s_lo, s_hi, g_ab + (size_t)(j * 64 + g) * 20480 + w * 5120 + lane * 4);
                publish(&g_flagA[j * 32 + g], lane);
                TSTAMP0(6);
                const __nv_bfloat16* xp = P.x + (size_t)(g * 64 + 16 * w + (lane >> 2)) * D_ + j * 160 + (lane & 3) * 2;
#pragma unroll
                for (int t = 0; t < 20; t++) {
                    uint32_t lo = ldg32(xp + t * 8), hi = ldg32(xp + 8 * D_ + t * 8);
                    acc[4 * t] = bf_lo(lo); acc[4 * t + 1] = bf_hi(lo); acc[4 * t + 2] = bf_lo(hi); acc[4 * t + 3] = bf_hi(hi);
                }
                fence_regs(acc);
                bar_sync(BAR_TO0, 256);
                TSTAMP0(7);
                stream_run<64, true>(acc, sR, sB, bars, I_G2, B_FULLA, B_EMPTYA, lead);
                TSTAMP0(8);
                uint32_t hp[40];
#pragma unroll
                for (int i = 0; i < 40; i++) hp[i] = pack_bf16(acc[2 * i], acc[2 * i + 1]);
                bar_sync(BAR_WG0, 128);
                const uint32_t sa = sR + (20 * j + (lane >> 4)) * 1024 + (2 * w + ((lane >> 3) & 1)) * 128 + (lane & 7) * 16;
#pragma unroll
                for (int t = 0; t < 20; t += 2) stsm4(sa + t * 1024, hp[2 * t], hp[2 * t + 1], hp[2 * t + 2], hp[2 * t + 3]);
                fence_async_smem();
                mbar_arrive(bars + 8 * B_HOWN);
                uint8_t* hd = g_h + (size_t)g * 81920 + j * 20480 + w * 256 + lane * 4;
#pragma unroll
                for (int t = 0; t < 20; t++) { stg32(hd + t * 1024, hp[2 * t]); stg32(hd + t * 1024 + 128, hp[2 * t + 1]); }
                float s0 = 0.f, s1 = 0.f;
#pragma unroll
                for (int t = 0; t < 20; t++) { s0 += bf_lo(hp[2 * t]) + bf_hi(hp[2 * t]); s1 += bf_lo(hp[2 * t + 1]) + bf_hi(hp[2 * t + 1]); }
                s0 += __shfl_xor_sync(0xffffffffu, s0, 1); s1 += __shfl_xor_sync(0xffffffffu, s1, 1);
                s0 += __shfl_xor_sync(0xffffffffu, s0, 2); s1 += __shfl_xor_sync(0xffffffffu, s1, 2);
                s0 *= (1.0f / 160.0f); s1 *= (1.0f / 160.0f);
                float q0 = 0.f, q1 = 0.f;
#pragma unroll
                for (int t = 0; t < 20; t++) {
                    float a = bf_lo(hp[2 * t]) - s0, b = bf_hi(hp[2 * t]) - s0, c = bf_lo(hp[2 * t + 1]) - s1, d = bf_hi(hp[2 * t + 1]) - s1;
                    q0 = fmaf(a, a, q0); q0 = fmaf(b, b, q0); q1 = fmaf(c, c, q1); q1 = fmaf(d, d, q1);
                }
                q0 += __shfl_xor_sync(0xffffffffu, q0, 1); q1 += __shfl_xor_sync(0xffffffffu, q1, 1);
                q0 += __shfl_xor_sync(0xffffffffu, q0, 2); q1 += __shfl_xor_sync(0xffffffffu, q1, 2);
                if ((lane & 3) == 0) {
                    float2* sp = &g_stats[(g * 4 + j) * 64 + 16 * w + (lane >> 2)];
                    sp[0] = make_float2(s0, q0); sp[8] = make_float2(s1, q1);
                }
                publish(&g_flagH[g * 32 + j], lane);
                TSTAMP0(9);
            }
            RowStat st;
            {
                float acc[128];
                bar_sync(BAR_TO0, 256);
                TSTAMP0(10);
                g3_run(acc, sR, sB, bars, I_S2Q, j, 0, 1, true, false, BAR_TO1, lead);
                st = load_stats(g, w, lane, tgt4);
                bar_sync(BAR_TO0, 256);
                TSTAMP0(11);
                g3_run(acc, sR, sB, bars, I_S2R, j, 1, 4, false, true, BAR_TO1, lead);
                TSTAMP0(12);
                g3_epilogue<0, 16, 64>(acc, st, sCS, 128, g_act + (size_t)(g * 216 + (j * 6 + 2) * 8) * 1024 + w * 256 + lane * 4, lane);
                publish(&g_flagAct[g * 32 + 4 + j], lane);
                TSTAMP0(13);
            }
            {
                float acc[56];
                bar_sync(BAR_TO0, 256);
                TSTAMP0(14);
                Ring rb(I_S4, NB);
                int prev = -1;
#pragma unroll 1
                for (int c = 0; c < 10; c++) {
                    mbar_wait(bars + 8 * (B_FULLB + rb.s), rb.ph);
                    uint64_t da = DH_BLK_A | (uint64_t)((sR + c * 8192) >> 4), db = DH_W64 | (uint64_t)((sB + rb.s * BSLOT) >> 4);
                    wg_fence();
                    wgmma_n112<1>(acc, da, db, c > 0);
                    wgmma_n112<1>(acc, da + 128, db + 128, 1);
                    wgmma_n112<1>(acc, da + 256, db + 256, 1);
                    wgmma_n112<1>(acc, da + 384, db + 384, 1);
                    wg_commit();
                    if (c == 9) bar_arrive(BAR_TO1, 256);
                    wg_wait<1>();
                    if (prev >= 0 && lead) { mbar_arrive(bars + 8 * (B_EMPTYB + prev)); mbar_arrive(bars + 8 * (B_EMPTYA2 + c - 1)); }
                    prev = rb.s;
                    rb.next<NB>();
                }
                wg_wait<0>();
                if (lead) { mbar_arrive(bars + 8 * (B_EMPTYB + prev)); mbar_arrive(bars + 8 * (B_EMPTYA2 + 9)); }
                fence_regs(acc);
                TSTAMP0(15);
                g3_epilogue<0, 6, 32>(acc, st, sCS, 384, g_act + (size_t)(g * 216 + 192 + 6 * j) * 1024 + w * 256 + lane * 4, lane);
                publish(&g_flagAct[g * 32 + 12 + j], lane);
                TSTAMP0(16);
            }
        } else {
            const int t128 = threadIdx.x & 127;
            {
                const int row = t128 >> 1, hf = t128 & 1;
                float q[4] = {0, 0, 0, 0};
#pragma unroll
                for (int c = 0; c < 5; c++)
#pragma unroll
                    for (int u = 0; u < 8; u++) {
                        uint4 v = lds128(sR + (hf * 5 + c) * 8192 + row * 128 + ((u ^ (hf * 4) ^ (row & 7)) * 16));
                        float a;
                        a = bf_lo(v.x); q[0] = fmaf(a, a, q[0]); a = bf_hi(v.x); q[1] = fmaf(a, a, q[1]);
                        a = bf_lo(v.y); q[2] = fmaf(a, a, q[2]); a = bf_hi(v.y); q[3] = fmaf(a, a, q[3]);
                        a = bf_lo(v.z); q[0] = fmaf(a, a, q[0]); a = bf_hi(v.z); q[1] = fmaf(a, a, q[1]);
                        a = bf_lo(v.w); q[2] = fmaf(a, a, q[2]); a = bf_hi(v.w); q[3] = fmaf(a, a, q[3]);
                    }
                float ss = (q[0] + q[1]) + (q[2] + q[3]);
                ss += __shfl_xor_sync(0xffffffffu, ss, 1);
                const float dl = lds32f(sLN + row * 4);
                const float var = fmaxf(ss * (1.0f / 640.0f) - dl * dl, 0.f);
                if (hf == 0) sts32f(sLN + 256 + row * 4, rsqrtf(var + 1e-5f));
                bar_sync(BAR_WG1, 128);
                bar_arrive(BAR_RSTD, 256);
            }
            TSTAMP0(20);
            {
                float acc[80];
                bar_sync(BAR_TO1, 256);
                TSTAMP0(21);
                g1_run(acc, sR, sB, bars, I_G1B, BAR_TO0, lead, true);
                TSTAMP0(22);
                const float s_lo = -lds32f(sLN + 256 + (16 * w + (lane >> 2)) * 4), s_hi = -lds32f(sLN + 256 + (16 * w + 8 + (lane >> 2)) * 4);
                g1_epilogue(acc, s_lo, s_hi, g_ab + (size_t)(j * 64 + 32 + g) * 20480 + w * 5120 + lane * 4);
                publish(&g_flagB[j * 32 + g], lane);
                TSTAMP0(23);
            }
            {
                const int wid = slot * 4 + w;
                if (wid < 432) {
                    const int mat = wid / 216, rem = wid - mat * 216, atom = rem >> 3, part = rem & 7;
                    const __nv_bfloat16* wp = (mat ? P.w_up : P.w_gate) + (size_t)(part * 80 + (lane >> 3)) * F_ + atom * 64 + (lane & 7) * 8;
                    uint4 v[20];
#pragma unroll
                    for (int i = 0; i < 20; i++) v[i] = ldg128(wp + (size_t)i * 4 * F_);
                    float s[8] = {0, 0, 0, 0, 0, 0, 0, 0};
#pragma unroll
                    for (int i = 0; i < 20; i++) {
                        s[0] += bf_lo(v[i].x); s[1] += bf_hi(v[i].x); s[2] += bf_lo(v[i].y); s[3] += bf_hi(v[i].y);
                        s[4] += bf_lo(v[i].z); s[5] += bf_hi(v[i].z); s[6] += bf_lo(v[i].w); s[7] += bf_hi(v[i].w);
                    }
#pragma unroll
                    for (int i = 0; i < 8; i++) { s[i] += __shfl_xor_sync(0xffffffffu, s[i], 8); s[i] += __shfl_xor_sync(0xffffffffu, s[i], 16); }
                    if (lane < 8) {
                        float4* dp = (float4*)&g_csum[part * 3456 + mat * F_ + atom * 64 + lane * 8];
                        dp[0] = make_float4(s[0], s[1], s[2], s[3]); dp[1] = make_float4(s[4], s[5], s[6], s[7]);
                    }
                }
                const int wid2 = 511 - wid;
                if (wid2 < 432) {
                    const int kg = wid2 >> 1, hf = wid2 & 1;
                    const __nv_bfloat16* wp = P.w_down + (size_t)(kg * 8 + (lane & 7)) * D_ + hf * 320 + (lane >> 3) * 8;
                    uint4 v[10];
#pragma unroll
                    for (int i = 0; i < 10; i++) v[i] = ldg128(wp + i * 32);
#pragma unroll
                    for (int i = 0; i < 10; i++)
                        stg128(g_wd + (size_t)((hf * 2 + i / 5) * 216 + kg) * 2560 + ((i % 5) * 4 + (lane >> 3)) * 128 + (lane & 7) * 16, v[i]);
                }
                publish(&g_flagAux[0], lane);
                TSTAMP0(24);
                uint32_t it = 0;
                while (ld_acquire(&g_flagAux[0]) != epoch * 512u) { __nanosleep(200); if (++it > (1u << 22)) __trap(); }
                for (int i = t128; i < 864; i += 128) {
                    const int mat = i >= 432, c = i - mat * 432;
                    const int col = mat * F_ + (c < 384 ? j * 384 + c : 1536 + 48 * j + (c - 384));
                    float s = 0.f;
#pragma unroll
                    for (int p = 0; p < 8; p++) s += __ldcg(&g_csum[p * 3456 + col]);
                    sts32f(sCS + i * 4, s);
                }
                bar_sync(BAR_WG1, 128);
                TSTAMP0(25);
            }
            RowStat st;
            uint32_t hp[40];
            {
                float acc[128];
                mbar_wait(bars + 8 * B_HOWN, 0);
                TSTAMP0(26);
                g3_run(acc, sR, sB, bars, I_S1Q, j, 0, 1, true, false, BAR_TO0, lead);
                bar_sync(BAR_TO1, 256);
                TSTAMP0(27);
                g3_run(acc, sR, sB, bars, I_S1R, j, 1, 4, false, true, BAR_TO0, lead);
                TSTAMP0(28);
                st = load_stats(g, w, lane, tgt4);
                g3_epilogue<0, 16, 64>(acc, st, sCS, 0, g_act + (size_t)(g * 216 + (j * 6) * 8) * 1024 + w * 256 + lane * 4, lane);
                publish(&g_flagAct[g * 32 + j], lane);
                TSTAMP0(29);
                bar_sync(BAR_TO1, 256);
                TSTAMP0(30);
                g3_run(acc, sR, sB, bars, I_S3, j, 0, 4, true, false, BAR_TO0, lead);
                TSTAMP0(31);
                if (lead) mbar_arrive(bars + 8 * B_RFREE);
                uint8_t* ad = g_act + (size_t)(g * 216 + (j * 6 + 4) * 8) * 1024 + w * 256 + lane * 4;
                g3_epilogue<0, 8, 64>(acc, st, sCS, 256, ad, lane);
                const uint8_t* hd = g_h + (size_t)g * 81920 + j * 20480 + w * 256 + lane * 4;
#pragma unroll
                for (int t = 0; t < 20; t++) { hp[2 * t] = ldcg32(hd + t * 1024); hp[2 * t + 1] = ldcg32(hd + t * 1024 + 128); }
                g3_epilogue<8, 16, 64>(acc, st, sCS, 256, ad, lane);
                publish(&g_flagAct[g * 32 + 8 + j], lane);
                TSTAMP0(32);
            }
            {
                float acc[80];
#pragma unroll
                for (int i = 0; i < 40; i++) { acc[2 * i] = bf_lo(hp[i]); acc[2 * i + 1] = bf_hi(hp[i]); }
                fence_regs(acc);
                bar_sync(BAR_TO1, 256);
                TSTAMP0(33);
                stream_run<27, false>(acc, sR, sB, bars, I_G4, B_FULLA2, B_EMPTYA2, lead);
                TSTAMP0(34);
                const uint32_t stg = sB + w * (16 * 336);
                const uint32_t sa = stg + ((lane & 7) + ((lane >> 3) & 1) * 8) * 336 + (lane >> 4) * 16;
#pragma unroll
                for (int t = 0; t < 20; t += 2)
                    stsm4(sa + t * 16, pack_bf16(acc[4 * t], acc[4 * t + 1]), pack_bf16(acc[4 * t + 2], acc[4 * t + 3]),
                          pack_bf16(acc[4 * t + 4], acc[4 * t + 5]), pack_bf16(acc[4 * t + 6], acc[4 * t + 7]));
                __syncwarp();
                __nv_bfloat16* op = P.out + (size_t)(g * 64 + 16 * w) * D_ + j * 160;
#pragma unroll
                for (int i = 0; i < 10; i++) {
                    const int e = i * 32 + lane, r = e / 20, u = e - r * 20;
                    stg128(op + r * D_ + u * 8, lds128(stg + r * 336 + u * 16));
                }
                if (lead) g_epoch[slot] = epoch;
                TSTAMP0(35);
            }
        }
    }
}

typedef CUresult (*EncodeFn)(CUtensorMap*, CUtensorMapDataType, cuuint32_t, void*, const cuuint64_t*, const cuuint64_t*,
                             const cuuint32_t*, const cuuint32_t*, CUtensorMapInterleave, CUtensorMapSwizzle,
                             CUtensorMapL2promotion, CUtensorMapFloatOOBfill);

void make2d(EncodeFn enc, CUtensorMap* m, const void* p, uint64_t d0, uint64_t d1, uint32_t b0, uint32_t b1) {
    cuuint64_t dims[2] = {d0, d1}, strides[1] = {d0 * 2};
    cuuint32_t box[2] = {b0, b1}, es[2] = {1, 1};
    enc(m, CU_TENSOR_MAP_DATA_TYPE_BFLOAT16, 2, const_cast<void*>(p), dims, strides, box, es, CU_TENSOR_MAP_INTERLEAVE_NONE,
        CU_TENSOR_MAP_SWIZZLE_128B, CU_TENSOR_MAP_L2_PROMOTION_L2_128B, CU_TENSOR_MAP_FLOAT_OOB_FILL_NONE);
}
void make3d(EncodeFn enc, CUtensorMap* m, const void* p) {
    cuuint64_t dims[3] = {64, 640, 27}, strides[2] = {(cuuint64_t)F_ * 2, 128};
    cuuint32_t box[3] = {64, 32, 2}, es[3] = {1, 1, 1};
    enc(m, CU_TENSOR_MAP_DATA_TYPE_BFLOAT16, 3, const_cast<void*>(p), dims, strides, box, es, CU_TENSOR_MAP_INTERLEAVE_NONE,
        CU_TENSOR_MAP_SWIZZLE_128B, CU_TENSOR_MAP_L2_PROMOTION_L2_128B, CU_TENSOR_MAP_FLOAT_OOB_FILL_NONE);
}

}

extern "C" void kernel_launch(void* const* d_in, const int* in_sizes, int n_in, void* d_out, int out_size) {
    static EncodeFn enc = nullptr;
    static int nsm = 0;
    if (!enc) {
        void* fn = nullptr;
        cudaDriverEntryPointQueryResult st;
        cudaGetDriverEntryPoint("cuTensorMapEncodeTiled", &fn, cudaEnableDefault, &st);
        enc = (EncodeFn)fn;
        cudaFuncSetAttribute(fused_kernel, cudaFuncAttributeMaxDynamicSharedMemorySize, SMEM_BYTES);
        int dev = 0;
        cudaGetDevice(&dev);
        cudaDeviceGetAttribute(&nsm, cudaDevAttrMultiProcessorCount, dev);
    }
    Params P;
    P.x = (const __nv_bfloat16*)d_in[0];
    P.ws_re = (const __nv_bfloat16*)d_in[1];
    P.ws_im = (const __nv_bfloat16*)d_in[2];
    P.w_gate = (const __nv_bfloat16*)d_in[6];
    P.w_up = (const __nv_bfloat16*)d_in[7];
    P.w_down = (const __nv_bfloat16*)d_in[8];
    P.out = (__nv_bfloat16*)d_out;
    make2d(enc, &P.wdre, d_in[3], D_, D_, 64, 160);
    make2d(enc, &P.wdim, d_in[4], D_, D_, 64, 160);
    make2d(enc, &P.wsre, d_in[1], S_, S_, 64, 64);
    make2d(enc, &P.wsim, d_in[2], S_, S_, 64, 64);
    make3d(enc, &P.wg, d_in[6]);
    make3d(enc, &P.wu, d_in[7]);
    make2d(enc, &P.wg2, d_in[6], F_, D_, 64, 64);
    make2d(enc, &P.wu2, d_in[7], F_, D_, 64, 64);
    cudaLaunchConfig_t cfg = {};
    cfg.gridDim = dim3(nsm == 132 ? 132 : 128);
    cfg.blockDim = dim3(384);
    cfg.dynamicSmemBytes = SMEM_BYTES;
    cfg.stream = cudaStreamPerThread;
    cudaLaunchAttribute at[1];
    at[0].id = cudaLaunchAttributeCooperative;
    at[0].val.cooperative = 1;
    cfg.attrs = at;
    cfg.numAttrs = 1;
    cudaLaunchKernelEx(&cfg, fused_kernel, P);
}
```

```cpp
#include <cuda_runtime.h>
#include <cuda_bf16.h>
#include <cuda.h>
#include <stdint.h>

namespace {

constexpr int S_ = 2048, D_ = 640, F_ = 1728;
constexpr int NB = 7;
constexpr int BSLOT = 20480;
constexpr int OFF_B = 81920;
constexpr int OFF_CS = OFF_B + NB * BSLOT;
constexpr int OFF_ST2 = OFF_CS + 2 * 448 * 4;
constexpr int OFF_BAR = OFF_ST2 + 512;
constexpr int SMEM_BYTES = 232448;
static_assert(OFF_BAR + 512 + 1024 <= SMEM_BYTES, "layout");

constexpr int B_XFULL = 0  , B_EMPTY = 10, B_WROW = 17, B_FULL = 18, B_G2GO = 25, B_CRDY = 26  ,
              B_DEP = 28  , B_STAT2 = 33, B_FULLH = 33  , B_RXFREE = 37, B_RXFULL = 38, B_OWNA = 39,
              B_FULL2 = 40  ,
              B_EMPTY2 = 45  , B_HOWN = 50, B_WFREE = 51, B_PUB = 52  , B_COUNT = 59;
constexpr int PUB_H = 2, PUB_S1 = 3;

constexpr int I_G1A = 0, I_G1B = 10, I_S1Q = 21, I_S2Q = 26, I_S1R = 31, I_S2R = 46, I_S3 = 61, I_S4 = 81, I_G4 = 89;

constexpr uint32_t SPIN_LIMIT = 1u << 23, MBAR_LIMIT = 1u << 20;

struct __align__(1024) Scratch {
    uint8_t ab[4 * 64 * 20480];
    uint8_t h[32 * 81920];
    uint8_t act[32 * 216 * 1024];
    uint8_t wh[4 * 216 * 512];
    float csum[4 * 3456];
    float csq[4 * 896];
    uint2 wsum[2 * 640];
    uint4 stats[32 * 4 * 64];
    uint32_t flagAB[2 * 128 * 32];
    uint32_t flagG[128 * 32];
    uint32_t flagAux[32];
    uint32_t epoch[160];
};
__device__ Scratch g_scratch;
#define TSTAMP(i)
#define TSTAMP0(i)
#define TSTAMPP(i)
#define TDUMP()
#define CSTAMP0(i)

#define SPIN_CHECK(it, lim, code) { if (++(it) > (lim)) __trap(); }
#define POLL_NS 0
__device__ __forceinline__ void mbar_init(uint32_t bar, uint32_t cnt) { asm volatile("mbarrier.init.shared::cta.b64 [%0], %1;" :: "r"(bar), "r"(cnt) : "memory"); }
__device__ __forceinline__ void mbar_expect_tx(uint32_t bar, uint32_t bytes) { asm volatile("mbarrier.arrive.expect_tx.shared::cta.b64 _, [%0], %1;" :: "r"(bar), "r"(bytes) : "memory"); }
__device__ __forceinline__ void mbar_arrive_if(uint32_t bar, bool pred) {
    asm volatile("{ .reg .pred p; setp.ne.b32 p, %1, 0; @p mbarrier.arrive.shared::cta.b64 _, [%0]; }" :: "r"(bar), "r"((uint32_t)pred) : "memory");
}
__device__ __forceinline__ void mbar_arrive_cluster_if(uint32_t bar, bool pred) {
    asm volatile("{ .reg .pred p; setp.ne.b32 p, %1, 0; @p mbarrier.arrive.shared::cluster.b64 _, [%0]; }" :: "r"(bar), "r"((uint32_t)pred) : "memory");
}
__device__ __forceinline__ bool mbar_try(uint32_t bar, uint32_t parity) {
    uint32_t ok;
    asm volatile("{ .reg .pred p; mbarrier.try_wait.parity.shared::cta.b64 p, [%1], %2; selp.u32 %0, 1, 0, p; }" : "=r"(ok) : "r"(bar), "r"(parity) : "memory");
    return ok;
}
__device__ __forceinline__ bool mbar_test(uint32_t bar, uint32_t parity) {
    uint32_t ok;
    asm volatile("{ .reg .pred p; mbarrier.test_wait.parity.shared::cta.b64 p, [%1], %2; selp.u32 %0, 1, 0, p; }" : "=r"(ok) : "r"(bar), "r"(parity) : "memory");
    return ok;
}
__device__ __forceinline__ void mbar_wait(uint32_t bar, uint32_t parity) {
    uint32_t it = 0;
    while (!mbar_try(bar, parity)) SPIN_CHECK(it, MBAR_LIMIT, ((bar & 0xFFFFFF) - 1024 - OFF_BAR) / 8 + parity * 1000)
}
__device__ __forceinline__ void mbar_wait_hot(uint32_t bar, uint32_t parity, bool done = false) {
    asm volatile("{ .reg .pred p; setp.ne.b32 p, %2, 0;\n"
                 "W: @p bra.uni D; mbarrier.try_wait.parity.shared::cta.b64 p, [%0], %1; bra.uni W;\n"
                 "D: }" :: "r"(bar), "r"(parity), "r"((uint32_t)done) : "memory");
}
__device__ __forceinline__ bool elect_one() { uint32_t p; asm volatile("{ .reg .pred P; elect.sync _|P, 0xffffffff; selp.u32 %0, 1, 0, P; }" : "=r"(p)); return p; }
__device__ __forceinline__ void tma2d(uint32_t dst, const CUtensorMap* m, int c0, int c1, uint32_t bar) {
    asm volatile("cp.async.bulk.tensor.2d.shared::cluster.global.mbarrier::complete_tx::bytes [%0], [%1, {%3, %4}], [%2];"
        :: "r"(dst), "l"(m), "r"(bar), "r"(c0), "r"(c1) : "memory");
}
__device__ __forceinline__ void tma3d(uint32_t dst, const CUtensorMap* m, int c0, int c1, int c2, uint32_t bar) {
    asm volatile("cp.async.bulk.tensor.3d.shared::cluster.global.mbarrier::complete_tx::bytes [%0], [%1, {%3, %4, %5}], [%2];"
        :: "r"(dst), "l"(m), "r"(bar), "r"(c0), "r"(c1), "r"(c2) : "memory");
}
__device__ __forceinline__ void tma3d_both(uint32_t dst, const CUtensorMap* m, int c0, int c1, int c2, uint32_t bar) {
    asm volatile("cp.async.bulk.tensor.3d.shared::cluster.global.mbarrier::complete_tx::bytes.multicast::cluster [%0], [%1, {%3, %4, %5}], [%2], %6;"
        :: "r"(dst), "l"(m), "r"(bar), "r"(c0), "r"(c1), "r"(c2), "h"((uint16_t)3) : "memory");
}
__device__ __forceinline__ void bulk_ld(uint32_t dst, const void* src, uint32_t bytes, uint32_t bar) {
    asm volatile("cp.async.bulk.shared::cluster.global.mbarrier::complete_tx::bytes [%0], [%1], %2, [%3];"
        :: "r"(dst), "l"(src), "r"(bytes), "r"(bar) : "memory");
}
__device__ __forceinline__ void prefetch_tmap(const CUtensorMap* m) { asm volatile("prefetch.tensormap [%0];" :: "l"(m) : "memory"); }
__device__ __forceinline__ void fence_async_smem() { asm volatile("fence.proxy.async.shared::cta;" ::: "memory"); }
__device__ __forceinline__ void fence_async_global() { asm volatile("fence.proxy.async.global;" ::: "memory"); }
__device__ __forceinline__ uint32_t ld_acquire(const uint32_t* p) { uint32_t v; asm volatile("ld.acquire.gpu.global.u32 %0, [%1];" : "=r"(v) : "l"(p) : "memory"); return v; }
__device__ __forceinline__ void red_release(uint32_t* p) { asm volatile("red.release.gpu.global.add.u32 [%0], 1;" :: "l"(p) : "memory"); }
__device__ __forceinline__ void bar_sync(int id, int n) { __syncwarp(); asm volatile("bar.sync %0, %1;" :: "r"(id), "r"(n) : "memory"); }
__device__ __forceinline__ void bar_arrive(int id, int n) { __syncwarp(); asm volatile("bar.arrive %0, %1;" :: "r"(id), "r"(n) : "memory"); }
__device__ __forceinline__ void wg_fence() { asm volatile("wgmma.fence.sync.aligned;" ::: "memory"); }
__device__ __forceinline__ void wg_commit() { asm volatile("wgmma.commit_group.sync.aligned;" ::: "memory"); }
template <int N> __device__ __forceinline__ void wg_wait() { asm volatile("wgmma.wait_group.sync.aligned %0;" :: "n"(N) : "memory"); }
template <int N> __device__ __forceinline__ void fence_regs(float (&d)[N]) {
#pragma unroll
    for (int i = 0; i < N; i++) asm volatile("" : "+f"(d[i]) :: "memory");
}
__device__ __forceinline__ uint32_t pack_bf16(float lo, float hi) { uint32_t r; asm("cvt.rn.bf16x2.f32 %0, %1, %2;" : "=r"(r) : "f"(hi), "f"(lo)); return r; }
__device__ __forceinline__ float bf_lo(uint32_t w) { return __uint_as_float(w << 16); }
__device__ __forceinline__ float bf_hi(uint32_t w) { return __uint_as_float(w & 0xffff0000u); }
__device__ __forceinline__ void stg128(void* p, uint4 v) { asm volatile("st.global.v4.u32 [%0], {%1,%2,%3,%4};" :: "l"(p), "r"(v.x), "r"(v.y), "r"(v.z), "r"(v.w) : "memory"); }
__device__ __forceinline__ uint4 lds128(uint32_t a) { uint4 v; asm volatile("ld.shared.v4.u32 {%0,%1,%2,%3}, [%4];" : "=r"(v.x), "=r"(v.y), "=r"(v.z), "=r"(v.w) : "r"(a) : "memory"); return v; }
__device__ __forceinline__ float2 lds64f(uint32_t a) { float2 v; asm volatile("ld.shared.v2.f32 {%0,%1}, [%2];" : "=f"(v.x), "=f"(v.y) : "r"(a) : "memory"); return v; }
__device__ __forceinline__ float lds32f(uint32_t a) { float v; asm volatile("ld.shared.f32 %0, [%1];" : "=f"(v) : "r"(a) : "memory"); return v; }
__device__ __forceinline__ void stsm4(uint32_t a, uint32_t r0, uint32_t r1, uint32_t r2, uint32_t r3) {
    asm volatile("stmatrix.sync.aligned.m8n8.x4.shared.b16 [%0], {%1,%2,%3,%4};" :: "r"(a), "r"(r0), "r"(r1), "r"(r2), "r"(r3) : "memory");
}
__device__ __forceinline__ void ldsm4(uint32_t a, uint32_t& r0, uint32_t& r1, uint32_t& r2, uint32_t& r3) {
    asm volatile("ldmatrix.sync.aligned.m8n8.x4.shared.b16 {%0,%1,%2,%3}, [%4];" : "=r"(r0), "=r"(r1), "=r"(r2), "=r"(r3) : "r"(a) : "memory");
}

__device__ __forceinline__ void st_tag(void* p, float v, uint32_t tag) {
    asm volatile("{ .reg .b64 t; mov.b64 t, {%1, %2}; st.relaxed.gpu.global.b64 [%0], t; }" :: "l"(p), "r"(__float_as_uint(v)), "r"(tag) : "memory");
}
__device__ __forceinline__ uint2 ld_tag(const void* p) {
    uint2 v; asm volatile("{ .reg .b64 t; ld.relaxed.gpu.global.b64 t, [%2]; mov.b64 {%0, %1}, t; }" : "=r"(v.x), "=r"(v.y) : "l"(p) : "memory"); return v;
}
__device__ __forceinline__ uint4 ld_tag2(const void* p) {
    uint4 v; asm volatile("{ .reg .b64 t, u; ld.relaxed.gpu.global.v2.b64 {t, u}, [%4]; mov.b64 {%0, %1}, t; mov.b64 {%2, %3}, u; }"
        : "=r"(v.x), "=r"(v.y), "=r"(v.z), "=r"(v.w) : "l"(p) : "memory"); return v;
}
__device__ __forceinline__ void stg32(void* p, uint32_t v) { asm volatile("st.global.u32 [%0], %1;" :: "l"(p), "r"(v) : "memory"); }
__device__ __forceinline__ uint32_t clk32() { uint32_t t; asm volatile("mov.u32 %0, %%clock;" : "=r"(t) :: "memory"); return t; }
__device__ __forceinline__ void sts32(uint32_t a, uint32_t v) { asm volatile("st.shared.u32 [%0], %1;" :: "r"(a), "r"(v) : "memory"); }
__device__ __forceinline__ float sum8(const uint4& v) {
    return ((bf_lo(v.x) + bf_hi(v.x)) + (bf_lo(v.y) + bf_hi(v.y))) + ((bf_lo(v.z) + bf_hi(v.z)) + (bf_lo(v.w) + bf_hi(v.w)));
}
__device__ __forceinline__ void spin_until(uint32_t t) { while ((int)(clk32() - t) < 0) {} }
__device__ __forceinline__ void mma16816(float (&c)[4], uint32_t a0, uint32_t a1, uint32_t a2, uint32_t a3, uint32_t b0, uint32_t b1) {
    asm volatile("mma.sync.aligned.m16n8k16.row.col.f32.bf16.bf16.f32 {%0,%1,%2,%3}, {%4,%5,%6,%7}, {%8,%9}, {%0,%1,%2,%3};"
        : "+f"(c[0]), "+f"(c[1]), "+f"(c[2]), "+f"(c[3]) : "r"(a0), "r"(a1), "r"(a2), "r"(a3), "r"(b0), "r"(b1));
}
__device__ __forceinline__ uint32_t add_bf16x2(uint32_t a, uint32_t b) { uint32_t r; asm("add.rn.bf16x2 %0, %1, %2;" : "=r"(r) : "r"(a), "r"(b)); return r; }
__device__ __forceinline__ float2 rowsum(const uint32_t (&v)[40]) {
    float c[4] = {0.f, 0.f, 0.f, 0.f};
#pragma unroll
    for (int i = 0; i < 40; i += 4) mma16816(c, v[i], v[i + 1], v[i + 2], v[i + 3], 0x3F803F80u, 0x3F803F80u);
    return make_float2(c[0], c[2]);
}

template <int TB>
__device__ __forceinline__ void wgmma_n160(float (&d)[80], uint64_t da, uint64_t db, int scaleD) {
    asm volatile("{ .reg .pred p; setp.ne.b32 p, %82, 0;\n"
        "wgmma.mma_async.sync.aligned.m64n160k16.f32.bf16.bf16 {%0,%1,%2,%3,%4,%5,%6,%7,%8,%9,%10,%11,%12,%13,%14,%15,%16,%17,%18,%19,%20,%21,%22,%23,%24,%25,%26,%27,%28,%29,%30,%31,%32,%33,%34,%35,%36,%37,%38,%39,%40,%41,%42,%43,%44,%45,%46,%47,%48,%49,%50,%51,%52,%53,%54,%55,%56,%57,%58,%59,%60,%61,%62,%63,%64,%65,%66,%67,%68,%69,%70,%71,%72,%73,%74,%75,%76,%77,%78,%79}, %80, %81, p, 1, 1, 0, %83; }"
        : "+f"(d[0]), "+f"(d[1]), "+f"(d[2]), "+f"(d[3]), "+f"(d[4]), "+f"(d[5]), "+f"(d[6]), "+f"(d[7]), "+f"(d[8]), "+f"(d[9]), "+f"(d[10]), "+f"(d[11]),
        "+f"(d[12]), "+f"(d[13]), "+f"(d[14]), "+f"(d[15]), "+f"(d[16]), "+f"(d[17]), "+f"(d[18]), "+f"(d[19]), "+f"(d[20]), "+f"(d[21]), "+f"(d[22]),
        "+f"(d[23]), "+f"(d[24]), "+f"(d[25]), "+f"(d[26]), "+f"(d[27]), "+f"(d[28]), "+f"(d[29]), "+f"(d[30]), "+f"(d[31]), "+f"(d[32]), "+f"(d[33]),
        "+f"(d[34]), "+f"(d[35]), "+f"(d[36]), "+f"(d[37]), "+f"(d[38]), "+f"(d[39]), "+f"(d[40]), "+f"(d[41]), "+f"(d[42]), "+f"(d[43]), "+f"(d[44]),
        "+f"(d[45]), "+f"(d[46]), "+f"(d[47]), "+f"(d[48]), "+f"(d[49]), "+f"(d[50]), "+f"(d[51]), "+f"(d[52]), "+f"(d[53]), "+f"(d[54]), "+f"(d[55]),
        "+f"(d[56]), "+f"(d[57]), "+f"(d[58]), "+f"(d[59]), "+f"(d[60]), "+f"(d[61]), "+f"(d[62]), "+f"(d[63]), "+f"(d[64]), "+f"(d[65]), "+f"(d[66]),
        "+f"(d[67]), "+f"(d[68]), "+f"(d[69]), "+f"(d[70]), "+f"(d[71]), "+f"(d[72]), "+f"(d[73]), "+f"(d[74]), "+f"(d[75]), "+f"(d[76]), "+f"(d[77]),
        "+f"(d[78]), "+f"(d[79])
        : "l"(da), "l"(db), "r"(scaleD), "n"(TB));
}
template <int TB>
__device__ __forceinline__ void wgmma_n256(float (&d)[128], uint64_t da, uint64_t db, int scaleD) {
    asm volatile("{ .reg .pred p; setp.ne.b32 p, %130, 0;\n"
        "wgmma.mma_async.sync.aligned.m64n256k16.f32.bf16.bf16 {%0,%1,%2,%3,%4,%5,%6,%7,%8,%9,%10,%11,%12,%13,%14,%15,%16,%17,%18,%19,%20,%21,%22,%23,%24,%25,%26,%27,%28,%29,%30,%31,%32,%33,%34,%35,%36,%37,%38,%39,%40,%41,%42,%43,%44,%45,%46,%47,%48,%49,%50,%51,%52,%53,%54,%55,%56,%57,%58,%59,%60,%61,%62,%63,%64,%65,%66,%67,%68,%69,%70,%71,%72,%73,%74,%75,%76,%77,%78,%79,%80,%81,%82,%83,%84,%85,%86,%87,%88,%89,%90,%91,%92,%93,%94,%95,%96,%97,%98,%99,%100,%101,%102,%103,%104,%105,%106,%107,%108,%109,%110,%111,%112,%113,%114,%115,%116,%117,%118,%119,%120,%121,%122,%123,%124,%125,%126,%127}, %128, %129, p, 1, 1, 0, %131; }"
        : "+f"(d[0]), "+f"(d[1]), "+f"(d[2]), "+f"(d[3]), "+f"(d[4]), "+f"(d[5]), "+f"(d[6]), "+f"(d[7]), "+f"(d[8]), "+f"(d[9]), "+f"(d[10]), "+f"(d[11]),
        "+f"(d[12]), "+f"(d[13]), "+f"(d[14]), "+f"(d[15]), "+f"(d[16]), "+f"(d[17]), "+f"(d[18]), "+f"(d[19]), "+f"(d[20]), "+f"(d[21]), "+f"(d[22]),
        "+f"(d[23]), "+f"(d[24]), "+f"(d[25]), "+f"(d[26]), "+f"(d[27]), "+f"(d[28]), "+f"(d[29]), "+f"(d[30]), "+f"(d[31]), "+f"(d[32]), "+f"(d[33]),
        "+f"(d[34]), "+f"(d[35]), "+f"(d[36]), "+f"(d[37]), "+f"(d[38]), "+f"(d[39]), "+f"(d[40]), "+f"(d[41]), "+f"(d[42]), "+f"(d[43]), "+f"(d[44]),
        "+f"(d[45]), "+f"(d[46]), "+f"(d[47]), "+f"(d[48]), "+f"(d[49]), "+f"(d[50]), "+f"(d[51]), "+f"(d[52]), "+f"(d[53]), "+f"(d[54]), "+f"(d[55]),
        "+f"(d[56]), "+f"(d[57]), "+f"(d[58]), "+f"(d[59]), "+f"(d[60]), "+f"(d[61]), "+f"(d[62]), "+f"(d[63]), "+f"(d[64]), "+f"(d[65]), "+f"(d[66]),
        "+f"(d[67]), "+f"(d[68]), "+f"(d[69]), "+f"(d[70]), "+f"(d[71]), "+f"(d[72]), "+f"(d[73]), "+f"(d[74]), "+f"(d[75]), "+f"(d[76]), "+f"(d[77]),
        "+f"(d[78]), "+f"(d[79]), "+f"(d[80]), "+f"(d[81]), "+f"(d[82]), "+f"(d[83]), "+f"(d[84]), "+f"(d[85]), "+f"(d[86]), "+f"(d[87]), "+f"(d[88]),
        "+f"(d[89]), "+f"(d[90]), "+f"(d[91]), "+f"(d[92]), "+f"(d[93]), "+f"(d[94]), "+f"(d[95]), "+f"(d[96]), "+f"(d[97]), "+f"(d[98]), "+f"(d[99]),
        "+f"(d[100]), "+f"(d[101]), "+f"(d[102]), "+f"(d[103]), "+f"(d[104]), "+f"(d[105]), "+f"(d[106]), "+f"(d[107]), "+f"(d[108]), "+f"(d[109]),
        "+f"(d[110]), "+f"(d[111]), "+f"(d[112]), "+f"(d[113]), "+f"(d[114]), "+f"(d[115]), "+f"(d[116]), "+f"(d[117]), "+f"(d[118]), "+f"(d[119]),
        "+f"(d[120]), "+f"(d[121]), "+f"(d[122]), "+f"(d[123]), "+f"(d[124]), "+f"(d[125]), "+f"(d[126]), "+f"(d[127])
        : "l"(da), "l"(db), "r"(scaleD), "n"(TB));
}
template <int TB>
__device__ __forceinline__ void wgmma_n128(float (&d)[64], uint64_t da, uint64_t db, int scaleD) {
    asm volatile("{ .reg .pred p; setp.ne.b32 p, %66, 0;\n"
        "wgmma.mma_async.sync.aligned.m64n128k16.f32.bf16.bf16 {%0,%1,%2,%3,%4,%5,%6,%7,%8,%9,%10,%11,%12,%13,%14,%15,%16,%17,%18,%19,%20,%21,%22,%23,%24,%25,%26,%27,%28,%29,%30,%31,%32,%33,%34,%35,%36,%37,%38,%39,%40,%41,%42,%43,%44,%45,%46,%47,%48,%49,%50,%51,%52,%53,%54,%55,%56,%57,%58,%59,%60,%61,%62,%63}, %64, %65, p, 1, 1, 0, %67; }"
        : "+f"(d[0]), "+f"(d[1]), "+f"(d[2]), "+f"(d[3]), "+f"(d[4]), "+f"(d[5]), "+f"(d[6]), "+f"(d[7]), "+f"(d[8]), "+f"(d[9]), "+f"(d[10]), "+f"(d[11]),
        "+f"(d[12]), "+f"(d[13]), "+f"(d[14]), "+f"(d[15]), "+f"(d[16]), "+f"(d[17]), "+f"(d[18]), "+f"(d[19]), "+f"(d[20]), "+f"(d[21]), "+f"(d[22]),
        "+f"(d[23]), "+f"(d[24]), "+f"(d[25]), "+f"(d[26]), "+f"(d[27]), "+f"(d[28]), "+f"(d[29]), "+f"(d[30]), "+f"(d[31]), "+f"(d[32]), "+f"(d[33]),
        "+f"(d[34]), "+f"(d[35]), "+f"(d[36]), "+f"(d[37]), "+f"(d[38]), "+f"(d[39]), "+f"(d[40]), "+f"(d[41]), "+f"(d[42]), "+f"(d[43]), "+f"(d[44]),
        "+f"(d[45]), "+f"(d[46]), "+f"(d[47]), "+f"(d[48]), "+f"(d[49]), "+f"(d[50]), "+f"(d[51]), "+f"(d[52]), "+f"(d[53]), "+f"(d[54]), "+f"(d[55]),
        "+f"(d[56]), "+f"(d[57]), "+f"(d[58]), "+f"(d[59]), "+f"(d[60]), "+f"(d[61]), "+f"(d[62]), "+f"(d[63])
        : "l"(da), "l"(db), "r"(scaleD), "n"(TB));
}
template <int TB>
__device__ __forceinline__ void wgmma_n32(float (&d)[16], uint64_t da, uint64_t db, int scaleD) {
    asm volatile("{ .reg .pred p; setp.ne.b32 p, %18, 0;\n"
        "wgmma.mma_async.sync.aligned.m64n32k16.f32.bf16.bf16 {%0,%1,%2,%3,%4,%5,%6,%7,%8,%9,%10,%11,%12,%13,%14,%15}, %16, %17, p, 1, 1, 0, %19; }"
        : "+f"(d[0]), "+f"(d[1]), "+f"(d[2]), "+f"(d[3]), "+f"(d[4]), "+f"(d[5]), "+f"(d[6]), "+f"(d[7]), "+f"(d[8]), "+f"(d[9]), "+f"(d[10]), "+f"(d[11]),
        "+f"(d[12]), "+f"(d[13]), "+f"(d[14]), "+f"(d[15])
        : "l"(da), "l"(db), "r"(scaleD), "n"(TB));
}

constexpr uint64_t desc_hi(uint32_t lbo, uint32_t sbo, uint32_t mode) {
    return ((uint64_t)(lbo >> 4) << 16) | ((uint64_t)(sbo >> 4) << 32) | ((uint64_t)mode << 62);
}
constexpr uint64_t DH_SW128_K = desc_hi(16, 1024, 1);
constexpr uint64_t DH_BLK_A = desc_hi(1024, 128, 0);
constexpr uint64_t DH_BLK_B = desc_hi(2560, 128, 0);
constexpr uint64_t DH_W32 = desc_hi(4096, 1024, 1);
constexpr uint64_t DH_W80 = desc_hi(10240, 1024, 1);
constexpr uint64_t DH_W64 = desc_hi(8192, 1024, 1);
constexpr uint64_t DH_BLK_H = desc_hi(512, 128, 0);

__host__ __device__ constexpr uint32_t full_bar(int idx) { return idx < I_G1B ? B_XFULL + idx : B_FULL + idx % NB; }
__host__ __device__ constexpr uint32_t full_ph(int idx) { return idx < I_G1B ? 0 : ((idx - I_G1B) / NB) & 1; }
struct Ring {
    uint32_t s, ph;
    __device__ __forceinline__ Ring(int idx) : s(idx % NB), ph((idx / NB) & 1) {}
    __device__ __forceinline__ void next() { if (++s == NB) { s = 0; ph ^= 1; } }
};

struct Params {
    Scratch* s;
    const __nv_bfloat16 *xp, *wd_re, *wd_im, *w_gate, *w_up, *w_down;
    __nv_bfloat16* out;
    uint32_t zero;
    CUtensorMap x, wdre, wdim, wsre, wsim, wg, wu, wg1, wu1, wd, wdh;
};

struct RowStat { float nm[2], k1[2], k2[2], iv[2]; };

__device__ __forceinline__ float link(float dep, uint32_t z, float v) {
    uint32_t r; asm("lop3.b32 %0, %1, %2, %3, 0xEA;" : "=r"(r) : "r"(__float_as_uint(dep)), "r"(z), "r"(__float_as_uint(v))); return __uint_as_float(r);
}
__device__ __forceinline__ float ex2(float t) { float e; asm("ex2.approx.ftz.f32 %0, %1;" : "=f"(e) : "f"(t)); return e; }
__device__ __forceinline__ float rcp(float t) { float e; asm("rcp.approx.ftz.f32 %0, %1;" : "=f"(e) : "f"(t)); return e; }

#define ZINIT 1
#define G1STATIC 0
#define G2_PRIO 2
#define PERRD 0
#define EARLY 1
#define H_DELAY 0
#define G2_RND 0
#define TANHV 0
#define LINKV 0
template <int NT>
__device__ __forceinline__ void g3_epilogue(const float (&acc)[8 * NT], const RowStat& st, uint32_t cg, uint8_t* dst, uint32_t z) {
    constexpr int UOFF = 4 * NT;
    float dep[2] = {0.f, 0.f};
#pragma unroll
    for (int t = 0; t < NT; t++) {
        const uint4 c4 = lds128(cg + t * 64);
#pragma unroll
        for (int h = 0; h < 2; h++) {
            const float nm = st.nm[h];
            const float g0 = fmaf(nm, __uint_as_float(c4.x), acc[4 * t + 2 * h]), g1 = fmaf(nm, __uint_as_float(c4.y), acc[4 * t + 2 * h + 1]);
            const float u0 = fmaf(nm, __uint_as_float(c4.z), acc[UOFF + 4 * t + 2 * h]), u1 = fmaf(nm, __uint_as_float(c4.w), acc[UOFF + 4 * t + 2 * h + 1]);
            const float t1 = g1 * fmaf(g1 * g1, st.k2[h], st.k1[h]);
            const float e0 = ex2(g0 * fmaf(g0 * g0, st.k2[h], st.k1[h])), e1 = ex2(t1);
            const float r0 = rcp(fmaf(e0, st.iv[h], st.iv[h])), r1 = rcp(fmaf(e1, st.iv[h], st.iv[h]));
            stg32(dst + t * 1024 + h * 128, pack_bf16((g0 * u0) * r0, (g1 * u1) * r1));
            dep[h] = e1;
        }
    }
}

__device__ __forceinline__ void warp_arrive(uint32_t bar, int lane) { __syncwarp(); mbar_arrive_if(bar, lane == 0); }

struct Rel { uint32_t bars, dual; bool two; };
__device__ __forceinline__ void release(const Rel& r, int idx, bool pred = true) {
    if (idx + NB >= I_S1Q && idx + NB < I_G4) mbar_arrive_cluster_if(r.dual + 8 * (B_EMPTY + idx % NB), r.two && pred);
    else mbar_arrive_if(r.bars + 8 * (B_EMPTY + idx % NB), r.two && pred);
}
template <bool PROBE, bool RELEASE, class F>
__device__ __forceinline__ void stage(uint32_t next_full, uint32_t next_ph, bool skip_probe, const Rel& r, int prev, bool rel, int hand_id, F mma) {
    bool ok = true;
    if (PROBE) ok = mbar_test(next_full, next_ph) || skip_probe;
    wg_fence();
    mma();
    wg_commit();
    if (hand_id >= 0) bar_arrive(hand_id, 256);
    wg_wait<1>();
    if (RELEASE) release(r, prev, rel);
    if (PROBE) mbar_wait_hot(next_full, next_ph, ok);
}
template <int I0, int N, bool FINISH = true, class F>
__device__ __forceinline__ void consume(const Rel& r, int hand_id, F mma) {
    const uint32_t bars = r.bars;
    mbar_wait_hot(bars + 8 * full_bar(I0), full_ph(I0));
#pragma unroll
    for (int i = 0; i < N; i++) {
        const uint32_t nf = bars + 8 * full_bar(I0 + i + 1), np = full_ph(I0 + i + 1);
        auto f = [&]() { mma(i, (I0 + i) % NB); };
        if (i == 0) stage<true, false>(nf, np, false, r, 0, true, -1, f);
        else if (i == N - 1) stage<false, true>(nf, np, false, r, I0 + i - 1, true, -1, f);
        else stage<true, true>(nf, np, false, r, I0 + i - 1, true, i == N - 2 ? hand_id : -1, f);
    }
    if (FINISH) {
        wg_wait<0>();
        release(r, I0 + N - 1);
    }
}
template <int I0, int N, bool FINISH = true, class F>
__device__ __forceinline__ void consume_laps(const Rel& r, int hand_id, F mma) {
    const uint32_t bars = r.bars;
    constexpr int PEEL = N % NB == 1, LAPS = (N + 1) / NB, LAST = NB - 2 + 2 * PEEL;
    static_assert(N % NB == 1 || N % NB == NB - 1, "lap structure");
    mbar_wait_hot(bars + 8 * full_bar(I0), full_ph(I0));
    if (I0 == I_S1R) mbar_wait_hot(bars + 8 * (B_FULLH + 1), 0);
    if (PEEL) stage<true, false>(bars + 8 * full_bar(I0 + 1), full_ph(I0 + 1), false, r, 0, true, -1, [&]() { mma(0, 0, I0 % NB); });
#pragma unroll 1
    for (int lap = 0; lap < LAPS; lap++) {
#pragma unroll
        for (int i = PEEL; i < NB + PEEL; i++) {
            if (!PEEL && i == NB - 1 && lap == LAPS - 1) break;
            if (I0 == I_S1R && (i == 3 || i == 5)) mbar_wait_hot(bars + 8 * (B_FULLH + (i == 5 ? 2 : 3)), 0, lap != (i == 3));
            stage<true, true>(bars + 8 * full_bar(I0 + i + 1), full_ph(I0 + i + 1) ^ (lap & 1), i == LAST && lap == LAPS - 1,
                              r, I0 + i + NB - 1, i || lap, i == LAST - 1 && lap == LAPS - 1 ? hand_id : -1, [&]() { mma(lap, i, (I0 + i) % NB); });
        }
    }
    if (FINISH) {
        wg_wait<0>();
        release(r, I0 + N - 1);
    }
}

template <int DT, class F>
__device__ __forceinline__ void produce(uint32_t lp, uint32_t cnt, Ring& rb, uint32_t bars, F issue) {
    uint32_t t = 0, kk = 0;
#pragma unroll 1
    for (uint32_t i = 0; i < cnt; i++) {
        mbar_wait(bars + 8 * (B_EMPTY + rb.s), rb.ph ^ 1);
        if (DT) {
            if (i == 0) {
                const uint32_t m0 = (__shfl_sync(0xffffffffu, clk32(), 0) + DT - lp * DT) / (2 * DT + !DT);
                t = m0 * (2 * DT) + lp * DT;
                kk = m0 & (cnt - 1);
            } else spin_until(t);
        }
        if (elect_one()) issue(2 * kk + lp, rb.s, bars + 8 * (B_FULL + rb.s));
        __syncwarp();
        t += 2 * DT;
        if (++kk == cnt) kk = 0;
        rb.s += 2; if (rb.s >= NB) { rb.s -= NB; rb.ph ^= 1; }
    }
}

#define B_DELAY 0
#define B_PACE 200
#define SP_DELAY 4000
#define PF_N 30
#define DT_G4 352
#define GC_DELAY 2000
#define G1B_DELAY 0
#define DT_G1 320
#define PF_OWN 6000
#define PF_D 3
#define PF_START 10000
#define DT160 320
constexpr int BAR_TO0 = 2, BAR_TO1 = 3, BAR_WG0 = 4, BAR_WG1 = 5, BAR_STAT = 6, BAR_P = 7;

__global__ void __cluster_dims__(2, 1, 1) __launch_bounds__(384, 1) fused_kernel(const __grid_constant__ Params P) {
    extern __shared__ __align__(1024) uint8_t smem_raw[];
    const uint32_t sraw = (uint32_t)__cvta_generic_to_shared(smem_raw);
    if ((sraw & 0xFFFFFFu) > 1024u) __trap();
    constexpr uint32_t dR = 1024, dB = dR + OFF_B;
    uint32_t cb;
    asm volatile("and.b32 %0, %1, 0xFF000000;" : "=r"(cb) : "r"(sraw));
    const uint32_t sR = cb + dR, sB = sR + OFF_B, sCS = sR + OFF_CS, bars = sR + OFF_BAR;
    uint32_t rank;
    asm volatile("mov.u32 %0, %%cluster_ctarank;" : "=r"(rank));
    const int warp = __shfl_sync(0xffffffffu, (int)(threadIdx.x >> 5), 0), lane = threadIdx.x & 31;
    Scratch* const S = P.s;

    int slot;
    {
        uint32_t smid, nsmid;
        asm volatile("mov.u32 %0, %%smid;" : "=r"(smid));
        asm volatile("mov.u32 %0, %%nsmid;" : "=r"(nsmid));
        const uint32_t t = smid >> 1, u = t - 32, r = (u * 37) >> 8;
        const uint32_t tp = t < 32 ? ((t + 7) & 7) * 8 + (t >> 3) : t < 60 ? (u - r * 7) * 8 + 4 + r : t < 62 ? t + 4 : t - 2;
        slot = nsmid == 132 ? tp * 2 + rank : blockIdx.x;
        slot = __shfl_sync(0xffffffffu, slot, 0);
    }
    const int tp = (slot & 15) >> 1;
    const int j = (0xF924 >> (2 * tp)) & 3, g = (slot >> 4) * 4 + ((0xB8 >> tp) & 1) * 2 + (slot & 1);
    if (threadIdx.x == 10 * 32) sts32(bars + 8 * B_COUNT, slot);
    if (warp == 9 && slot < 128 && elect_one()) {
        mbar_init(bars + 8 * B_XFULL, 1); mbar_init(bars + 8 * B_WROW, 1);
        fence_async_smem();
        mbar_expect_tx(bars + 8 * B_XFULL, 28672);
        tma2d(sR, &P.x, 0, g * 64, bars + 8 * B_XFULL);
        tma2d(sB, &P.wdre, 0, j * 160, bars + 8 * B_XFULL);
        mbar_expect_tx(bars + 8 * B_WROW, 6400);
        bulk_ld(sB + 6 * BSLOT, P.wd_re + (size_t)(j * 160 + g * 5) * D_, 6400, bars + 8 * B_WROW);
    }
    const uint32_t tstart = clk32();
    if (threadIdx.x == 11 * 32) {
#pragma unroll
        for (int i = B_XFULL + 1; i < B_WROW; i++) mbar_init(bars + 8 * i, i >= B_EMPTY ? 2 : 1);
        asm volatile("fence.mbarrier_init.release.cluster;" ::: "memory");
        fence_async_smem();
    } else if (threadIdx.x == 8 * 32) {
#pragma unroll
        for (int i = B_FULL; i < B_FULL2; i++) mbar_init(bars + 8 * i, 1);
        mbar_expect_tx(bars + 8 * B_RXFULL, 20480);
        asm volatile("fence.mbarrier_init.release.cluster;" ::: "memory");
        fence_async_smem();
    } else if (threadIdx.x == 10 * 32) {
#pragma unroll
        for (int i = B_FULL2; i < B_COUNT; i++) mbar_init(bars + 8 * i, i < B_EMPTY2 ? 1 : i < B_HOWN ? 2 : 4);
        mbar_arrive_if(bars + 8 * B_FULL2, true); mbar_arrive_if(bars + 8 * B_EMPTY2, true); mbar_arrive_if(bars + 8 * B_EMPTY2, true);
        fence_async_smem();
    }
    __syncthreads();
    if (warp == 10) asm volatile("barrier.cluster.arrive.release.aligned;" ::: "memory");
    else asm volatile("barrier.cluster.arrive.relaxed.aligned;" ::: "memory");
    if (slot >= 128) {
        const int q = slot - 128, tid = threadIdx.x;
        const uint32_t epoch = __ldcg(&S->epoch[slot]) + 1;
        Ring rb(0);
        constexpr int B_DONE = B_PUB;
        if (warp == 8) {
            spin_until(tstart + SP_DELAY);
#pragma unroll 1
            for (int it = -8; it < 64; it++) {
                if (it < 44) mbar_wait(bars + 8 * (B_DONE + rb.s), rb.ph ^ 1);
                if (elect_one()) {
                    if (it >= 40 && it < 44) {
                        mbar_expect_tx(bars + 8 * (B_FULL + rb.s), 27648);
                        tma3d(sR + rb.s * 27648, &P.wdh, 0, (2 * q + (it & 1)) * 216, it < 42 ? 2 : 7, bars + 8 * (B_FULL + rb.s));
                    } else if (it < 40) {
                        const uint32_t bytes = it < 0 ? 25600 : 27648;
                        mbar_expect_tx(bars + 8 * (B_FULL + rb.s), bytes);
                        bulk_ld(sR + rb.s * 27648, it < 0 ? P.wd_im + (size_t)(160 * q + 20 * (it + 8)) * D_
                                                          : (it < 20 ? P.w_gate : P.w_up - 160 * F_) + (size_t)(20 * q + it) * 8 * F_, bytes, bars + 8 * (B_FULL + rb.s));
                    } else asm volatile("cp.async.bulk.prefetch.L2.global [%0], %1;" :: "l"((const uint8_t*)P.w_down + (20 * q + it - 44) * 27648), "r"(27648) : "memory");
                }
                __syncwarp();
                rb.next();
            }
        } else if (warp < 8) {
            auto done = [&](uint32_t dep) {
                bar_sync(8 + (warp >> 1) + (dep & P.zero), 64);
                mbar_arrive_if(bars + 8 * (B_DONE + rb.s), (tid & 63) == 0);
                rb.next();
            };
#pragma unroll 1
            for (int n = 0; n < 8; n++) {
                const int row = min(tid >> 3, 19);
                uint32_t v[40];
                mbar_wait(bars + 8 * (B_FULL + rb.s), rb.ph);
#pragma unroll
                for (int i = 0; i < 10; i++) { const uint4 t = lds128(sR + rb.s * 27648 + row * 1280 + i * 128 + (lane & 7) * 16); v[4 * i] = t.x; v[4 * i + 1] = t.y; v[4 * i + 2] = t.z; v[4 * i + 3] = t.w; }
                done(v[39]);
                const float2 c = rowsum(v);
                float sw = c.x + c.y;
                sw += __shfl_xor_sync(0xffffffffu, sw, 4);
                if ((lane & 7) == 0 && tid < 160) st_tag(&S->wsum[640 + 160 * q + 20 * n + row], sw, epoch);
            }
            TSTAMP0(25);
            const uint32_t off = min(tid, 215) * 16;
#pragma unroll 1
            for (int mat = 0; mat < 2; mat++) {
                float s[8] = {0, 0, 0, 0, 0, 0, 0, 0};
#pragma unroll 1
                for (int n = 0; n < 20; n++) {
                    mbar_wait(bars + 8 * (B_FULL + rb.s), rb.ph);
#pragma unroll 4
                    for (int i = 0; i < 8; i++) {
                        const uint4 v = lds128(sR + rb.s * 27648 + i * 3456 + off);
                        s[0] += bf_lo(v.x); s[1] += bf_hi(v.x); s[2] += bf_lo(v.y); s[3] += bf_hi(v.y);
                        s[4] += bf_lo(v.z); s[5] += bf_hi(v.z); s[6] += bf_lo(v.w); s[7] += bf_hi(v.w);
                    }
                    done(__float_as_uint(s[7]));
                }
                float4* dp = (float4*)((uint8_t*)&S->csum[q * 3456 + mat * F_] + off * 2);
                dp[0] = make_float4(s[0], s[1], s[2], s[3]); dp[1] = make_float4(s[4], s[5], s[6], s[7]);
            }
            __syncwarp();
            if (lane == 0) red_release(&S->flagAux[0]);
            TSTAMP0(24);
            {
                uint32_t it = 0;
                while (ld_acquire(&S->flagAux[0]) != epoch * 32u) SPIN_CHECK(it, SPIN_LIMIT, 5004)
                if (tid < (q < 3 ? 224 : 192)) {
                    const int c = tid * 2;
                    const float* cp = &S->csum[c < 384 ? q * 384 + c : 1536 - 384 + 64 * q + c];
                    float4 o = make_float4(0.f, 0.f, 0.f, 0.f);
#pragma unroll
                    for (int p = 0; p < 4; p++) {
                        const float2 a = __ldcg((const float2*)(cp + p * 3456)), b = __ldcg((const float2*)(cp + p * 3456 + F_));
                        o.x += a.x; o.y += a.y; o.z += b.x; o.w += b.y;
                    }
                    ((float4*)&S->csq[q * 896])[tid] = o;
                }
            }
            __syncwarp();
            if (lane == 0) { fence_async_global(); red_release(&S->flagAux[1]); }
            TSTAMP0(23);
#pragma unroll 1
            for (int n = 0; n < 4; n++) {
                mbar_wait(bars + 8 * (B_FULL + rb.s), rb.ph);
#pragma unroll 1
                for (int task = warp; task < 54; task += 8) {
                    const int kg = task >> 1, hf = task & 1;
                    stg128(S->wh + (size_t)(((n >> 1) * 2 + hf) * 216 + (2 * q + (n & 1)) * 27 + kg) * 512 + lane * 16,
                           lds128(sR + rb.s * 27648 + kg * 1024 + (lane & 7) * 128 + (((hf * 4 + (lane >> 3)) ^ (lane & 7)) << 4)));
                }
                rb.next();
            }
            __syncwarp();
            if (lane == 0) { fence_async_global(); red_release(&S->flagAux[2]); }
            TSTAMP0(22);
            __syncwarp();
            TDUMP();
        }
        if (warp < 4) {
            uint32_t it = 0;
            while (ld_acquire(&S->flagAB[warp * (PERRD ? 1024 : 32) + lane]) != epoch) { __nanosleep(1000); SPIN_CHECK(it, (1u << 20), 5002) }
            if (threadIdx.x == 0) S->epoch[slot] = epoch;
        }
        return;
    }
    TSTAMP0(warp >> 2);

    if (warp >= 8) {
        if (warp & 1) {
            const uint32_t p = (warp >> 1) & 1;
            Ring rb(p);
            if (p == 0) rb.s = 2;
#pragma unroll 1
            for (int i = 2 - p; i < 20; i += 2) {
                mbar_wait(bars + 8 * (B_EMPTY + rb.s), rb.ph ^ 1);
                spin_until(tstart + i * DT_G1 + (i >= 10 ? G1B_DELAY : 0));
                if (i == 6) mbar_wait(bars + 8 * B_WFREE, 0);
                if (elect_one()) {
                    if (i < 10) {
                        mbar_expect_tx(bars + 8 * (B_XFULL + i), 28672);
                        tma2d(sR + i * 8192, &P.x, i * 64, g * 64, bars + 8 * (B_XFULL + i));
                        tma2d(sB + rb.s * BSLOT, &P.wdre, i * 64, j * 160, bars + 8 * (B_XFULL + i));
                    } else {
                        mbar_expect_tx(bars + 8 * (B_FULL + rb.s), 20480);
                        tma2d(sB + rb.s * BSLOT, &P.wdim, (i - 10) * 64, j * 160, bars + 8 * (B_FULL + rb.s));
                    }
                }
                __syncwarp();
                rb.s += 2; if (rb.s >= NB) { rb.s -= NB; rb.ph ^= 1; }
            }
            TSTAMPP(40);
            if (p == 0) {
                rb.s = 22 % NB; rb.ph = (22 / NB) & 1;
                uint32_t s = 1, ph = 0, t = 0;
                const uint32_t own = (g & 2) + rank;
#pragma unroll 1
                for (int seg = 0; seg < 6; seg++) {
                    const bool im = seg == 1 || seg > 3, rot = seg == 2 || seg == 5;
                    const uint32_t cnt = seg == 2 ? 14 : seg == 5 ? 12 : 1;
                    const uint32_t k0 = (rot ? 4 + rank : seg < 2 ? own : own ^ 2) + (g & ~3), bytes = seg == 1 ? 16384 : 36864;
                    const CUtensorMap* m = im ? &P.wsim : &P.wsre;
                    const uint8_t* src = S->ab + (size_t)(j * 64 + (im ? 32 : 0)) * 20480;
                    uint32_t u = 0;
                    if (!(seg & 1)) mbar_wait_hot(bars + 8 * (seg == 0 ? B_OWNA : seg == 2 ? B_G2GO : B_DEP), 0);
#pragma unroll 1
                    for (uint32_t i = 0; i < cnt; i++) {
                        mbar_wait(bars + 8 * (B_EMPTY2 + s), ph);
                        if (i == 0) {
                            const uint32_t m0 = (__shfl_sync(0xffffffffu, clk32(), 0) + (seg == 2 ? G2_RND : DT160)) / (2 * DT160);
                            t = m0 * (2 * DT160);
                            u = seg == 2 ? m0 % 14u : seg == 5 ? m0 % 12u : 0;
                        } else spin_until(t);
                        if (elect_one()) {
                            const uint32_t bar = bars + 8 * (B_FULL2 + s), k = (k0 + u * 2) & 31;
                            mbar_expect_tx(bar, bytes);
                            if (seg != 1) bulk_ld(sB + s * BSLOT, src + k * 20480, 20480, bar);
                            tma2d(sR + s * 16384, m, k * 64, g * 64, bar);
                            tma2d(sR + s * 16384 + 8192, m, k * 64, (g ^ 1) * 64, bar);
                        }
                        if (seg == 2 && i == 0) { TSTAMPP(41); }
                        if (seg == 0) { TSTAMPP(42); }
                        if (seg == 5 && i == 10) bar_arrive(BAR_P, 64);
                        __syncwarp();
                        t += 2 * DT160;
                        if (++u == cnt) u = 0;
                        if (++s == 5) { s = 0; ph ^= 1; }
                    }
                }
                mbar_arrive_if(bars + 8 * (B_FULL + 6), lane == 0);
            } else {
                bar_sync(BAR_P, 64);
#pragma unroll 1
                for (uint32_t s = 1; s < 5; s++) {
                    mbar_wait(bars + 8 * (B_EMPTY2 + s), 0);
                    if (elect_one()) {
                        const uint32_t bar = bars + 8 * (B_FULL2 + s), k = (27 + s + (g & ~3)) & 31;
                        mbar_expect_tx(bar, 28672);
                        bulk_ld(sB + s * BSLOT, S->ab + (size_t)(j * 64 + 32 + k) * 20480, 20480, bar);
                        tma2d(sR + s * 16384, &P.wsim, k * 64, g * 64, bar);
                    }
                    __syncwarp();
                }
                mbar_wait(bars + 8 * (B_EMPTY + 1), 0);
                mbar_wait(bars + 8 * B_EMPTY2, 1);
                mbar_arrive_cluster_if((bars ^ (lane << 24)) + 8 * B_EMPTY, lane < 2);
            }
            const uint32_t lp = p ^ 1;
            produce<0>(lp, 30, rb, bars, [&](int k, uint32_t s, uint32_t bar) {
                const int sub = k < 10 ? k >= 5 : k < 40 ? k >= 25 : 2;
                int kk = j * 5 + (k >= 40 ? k - 40 : k < 10 ? k - 5 * sub : k - 5 - 15 * sub); if (kk >= 20) kk -= 20;
                mbar_expect_tx(bar, 16384);
                tma3d_both(sB + s * BSLOT + rank * 8192, rank ? &P.wu : &P.wg, 0, kk * 32, j * 6 + sub * 2, bar);
            });
            produce<0>(lp, 4, rb, bars, [&](int k, uint32_t s, uint32_t bar) {
                mbar_expect_tx(bar, 20480);
                tma3d_both(sB + s * BSLOT + rank * 10240, rank ? &P.wu1 : &P.wg1, 0, ((2 * j + k + 2) & 7) * 80, 24 + j, bar);
            });
            static_assert(I_S1Q % 2 && I_S4 % 2 && I_G4 % 2, "segment parity");
#pragma unroll 1
            for (int d = 0; d < 4; d++) {
                mbar_wait_hot(bars + 8 * (B_DEP + 1 + d), 0);
                produce<DT_G4>(lp, d < 3 ? 4 : 2 - lp, rb, bars, [&](int k, uint32_t s, uint32_t bar) {
                    const int atom = d < 3 ? (k >> 1) * 6 + 2 * d + (k & 1) : 24 + k;
                    mbar_expect_tx(bar, 28672);
                    bulk_ld(sR + (3 + (s >= I_G4 % NB ? s - I_G4 % NB : s + NB - I_G4 % NB)) * 8192, S->act + (size_t)(g * 27 + atom) * 8192, 8192, bar);
                    tma3d(sB + s * BSLOT, &P.wd, 0, atom * 64, (j * 5 + 1) >> 1, bar);
                    bulk_ld(sB + s * BSLOT + 16384, S->wh + (size_t)(j * 27 + atom) * 4096, 4096, bar);
                });
            }
        } else {
            const int im = warp == 8;
            const uint32_t* fA = &S->flagAB[(PERRD ? (j * 32 + g) * 32 : j * 32) + lane];
            const uint32_t* fB = fA + (PERRD ? 128 * 32 : 128);
            const uint32_t* fG = &S->flagG[(PERRD ? g * 4 + j : g) * 32];
            const uint32_t epoch = __ldcg(&S->epoch[slot]) + 1;
            if (lane == 0) { prefetch_tmap(im ? &P.wsre : &P.wdim); prefetch_tmap(&P.wsim); }
            auto gather_c = [&]() {
                const uint2* p = &S->wsum[im * 640 + j * 160 + lane];
                uint2 t[5];
                bool ok = true;
#pragma unroll
                for (int i = 0; i < 5; i++) { t[i] = ld_tag(p + 32 * i); ok = ok && t[i].y == epoch; }
                if (!__all_sync(0xffffffffu, ok)) return false;
#pragma unroll
                for (int i = 0; i < 5; i++) sts32(sCS + 512 + (im * 160 + 32 * i + lane) * 4, t[i].x);
                warp_arrive(bars + 8 * (B_CRDY + im), lane);
                TSTAMP(45 + im);
                return true;
            };
            uint32_t it = 0;
            if (warp == 8) {
            {
                spin_until(tstart + PF_OWN);
                if (lane == 0) asm volatile("cp.async.bulk.prefetch.tensor.2d.L2.global.tile [%0, {%1, %2}];" :: "l"((j & 1) ? &P.wsim : &P.wsre),
                                            "r"((int)(((g & ~1) + (j >> 1)) * 64)), "r"(g * 64) : "memory");
                spin_until(tstart + PF_START);
                uint32_t m = __shfl_sync(0xffffffffu, clk32(), 0) / (2 * DT160), todo = 0;
#pragma unroll 1
                for (int n = 0; n < 30 || todo < 2; n++, m++) {
                    spin_until(m * (2 * DT160));
                    if (n < PF_N && ((m ^ j) & 1) == 0 && lane == 0) {
                        const uint32_t u = n < 14 ? (m + PF_D) % 14u + 2 : n < 16 ? ((g >> 1) & 1) ^ 1 : n < 18 ? n - 2 : (m + PF_D) % 12u + 2;
                        asm volatile("cp.async.bulk.prefetch.tensor.2d.L2.global.tile [%0, {%1, %2}];" :: "l"(n < 15 ? &P.wsre : &P.wsim),
                                     "r"((int)(((u * 2 + (j >> 1) + (g & ~3)) & 31) * 64)), "r"(g * 64) : "memory");
                    }
                    if (todo == 0) todo = gather_c();
                    else if (todo == 1 && (EARLY || mbar_test(bars + 8 * (B_PUB + 1), 0)) &&
                             __all_sync(0xffffffffu, ld_acquire(fB) == epoch)) {
                        warp_arrive(bars + 8 * B_DEP, lane);
                        todo = 2;
                    }
                    SPIN_CHECK(it, SPIN_LIMIT >> 4, 5010)
                }
            }
            if (lane == 0) { prefetch_tmap(&P.wg); prefetch_tmap(&P.wu); prefetch_tmap(&P.wg1); prefetch_tmap(&P.wu1); prefetch_tmap(&P.wd); }
            uint32_t seen = EARLY ? __ballot_sync(0xffffffffu, ld_acquire(fG + ((j + lane) & 3)) == epoch) : 0;
            mbar_wait_hot(bars + 8 * B_HOWN, 0);
            {
                uint32_t todo = 0xE;
                it = 0;
                while (todo) {
                    const uint32_t rdy = (seen | __ballot_sync(0xffffffffu, ld_acquire(fG + ((j + lane) & 3)) == epoch)) & todo;
                    todo &= ~rdy;
                    if (elect_one()) {
#pragma unroll 1
                        for (int i = 1; i < 4; i++)
                            if ((rdy >> i) & 1) {
                                const int qq = (j + i) & 3;
                                mbar_expect_tx(bars + 8 * (B_FULLH + i), 20480);
                                bulk_ld(sR + i * 20480, S->h + (size_t)g * 81920 + qq * 20480, 20480, bars + 8 * (B_FULLH + i));
                            }
                    }
                    __syncwarp();
                    SPIN_CHECK(it, SPIN_LIMIT, 5005)
                }
            }
            TSTAMP(44);
            {
                const uint4* sp = &S->stats[g * 4 * 64 + lane];
                uint4 v[8];
                it = 0;
                while (true) {
                    bool ok = true;
#pragma unroll
                    for (int i = 0; i < 8; i++) { v[i] = ld_tag2(sp + i * 32); ok = ok && v[i].y == epoch && v[i].w == epoch; }
                    if (__all_sync(0xffffffffu, ok)) break;
                    __nanosleep(100);
                    SPIN_CHECK(it, SPIN_LIMIT, 5001)
                }
#pragma unroll
                for (int hf = 0; hf < 2; hf++) {
                    float m = 0.f, m2 = 0.f;
#pragma unroll
                    for (int i = 0; i < 4; i++) m += __uint_as_float(v[2 * i + hf].x);
                    m *= 0.25f;
#pragma unroll
                    for (int i = 0; i < 4; i++) { const float d = __uint_as_float(v[2 * i + hf].x) - m; m2 += fmaf(160.0f * d, d, __uint_as_float(v[2 * i + hf].z)); }
                    sts32(sR + OFF_ST2 + (hf * 32 + lane) * 4, __float_as_uint(m));
                    sts32(sR + OFF_ST2 + 256 + (hf * 32 + lane) * 4, __float_as_uint(m2 * (1.0f / 640.0f) + 1e-5f));
                }
            }
            it = 0;
            while (ld_acquire(&S->flagAux[1]) != epoch * 32u) { __nanosleep(100); SPIN_CHECK(it, SPIN_LIMIT, 5012) }
            __syncwarp();
            if (elect_one()) {
                mbar_expect_tx(bars + 8 * B_STAT2, 3584);
                bulk_ld(sCS, &S->csq[j * 896], 3584, bars + 8 * B_STAT2);
            }
            __syncwarp();
            TSTAMP(43);
            it = 0;
            while (ld_acquire(&S->flagAux[2]) != epoch * 32u) { __nanosleep(200); SPIN_CHECK(it, SPIN_LIMIT, 5013) }
#pragma unroll 1
            for (int d = 0; d < 4; d++) {
                mbar_wait_hot(bars + 8 * (B_PUB + PUB_S1 + d), 0);
                const uint32_t need = 0xF0000u << (4 * d);
                it = 0;
                while ((__ballot_sync(0xffffffffu, ld_acquire(fG + lane) == epoch) & need) != need) { if (POLL_NS) __nanosleep(POLL_NS); SPIN_CHECK(it, SPIN_LIMIT, 5006) }
                warp_arrive(bars + 8 * (B_DEP + 1 + d), lane);
                TSTAMP(60 + d);
            }
            } else {
                spin_until(tstart + GC_DELAY);
                while (!gather_c()) { __nanosleep(40); SPIN_CHECK(it, SPIN_LIMIT, 5007) }
                bool early = EARLY && __all_sync(0xffffffffu, ld_acquire(fA) == epoch);
#pragma unroll 1
                for (int k = 0; k < 7; k++) {
                    uint32_t* flag = k < 2 ? &S->flagAB[PERRD ? (k * 128 + j * 32 + lane) * 32 + g : k * 128 + j * 32 + g] : &S->flagG[(PERRD ? g * 4 + lane : g) * 32 + (k == PUB_H ? j : 16 + (k - PUB_S1) * 4 + j)];
                    mbar_wait(bars + 8 * (B_PUB + k), 0);
                    if (k == 1) {
                        uint32_t tb = clk32() + B_DELAY;
#pragma unroll 1
                        for (int i = 0; i < 8; i++) {
                            spin_until(tb); tb += B_PACE;
                            if (lane == 0) asm volatile("cp.async.bulk.global.shared::cta.bulk_group [%0], [%1], 2560;"
                                :: "l"(S->ab + (size_t)(j * 64 + 32 + g) * 20480 + i * 2560), "r"(sB + 5 * BSLOT + i * 2560) : "memory");
                        }
                        asm volatile("cp.async.bulk.commit_group;" ::: "memory");
                        asm volatile("cp.async.bulk.wait_group 0;" ::: "memory");
                    }
                    __syncwarp();
                    if (PERRD ? k < 2 || lane < 4 : lane == 0) {
                        fence_async_global();
                        asm volatile("st.release.gpu.global.u32 [%0], %1;" :: "l"(flag), "r"(epoch) : "memory");
                    }
                    __syncwarp();
                    TSTAMP(50 + k);
                    if (k == 1) {
                        asm volatile("barrier.cluster.wait.acquire.aligned;" ::: "memory");
                        if (lane == 0) {
                            uint32_t ps;
                            asm volatile("ld.shared::cluster.u32 %0, [%1];" : "=r"(ps) : "r"((bars + 8 * B_COUNT) ^ 0x1000000u) : "memory");
                            if (ps != (uint32_t)(slot ^ 1)) __trap();
                            asm volatile("mbarrier.arrive.release.cluster.shared::cluster.b64 _, [%0];" :: "r"((bars + 8 * B_RXFREE) ^ 0x1000000u) : "memory");
                        }
                    }
                    if (k == 0) {
                        warp_arrive(bars + 8 * B_OWNA, lane);
                        it = 0;
                                                while (!early && !__all_sync(0xffffffffu, ld_acquire(fA) == epoch)) SPIN_CHECK(it, SPIN_LIMIT, 5003)
                        TSTAMP(39);
                        warp_arrive(bars + 8 * B_G2GO, lane);
                    }
                }
            }
        }
    } else {
        const int w = warp & 3, wg = warp >> 2;
        const int t128 = threadIdx.x & 127;
        const bool lead = t128 == 0;
        const Rel rel = {bars, bars ^ ((uint32_t)(t128 == 1) << 24), t128 < 2};
        const uint32_t zero = P.zero;
        const uint32_t epoch = __ldcg(&S->epoch[slot]) + 1;
        if (wg == 1) {
            {
                const int wr = min(t128 >> 4, 4);
                mbar_wait_hot(bars + 8 * B_WROW, 0);
                uint4 v[5];
#pragma unroll
                for (int i = 0; i < 5; i++) v[i] = lds128(sB + 6 * BSLOT + wr * 1280 + i * 256 + (lane & 15) * 16);
                warp_arrive(bars + 8 * B_WFREE + (v[4].w & zero), lane);
                float sm = (sum8(v[0]) + sum8(v[1])) + (sum8(v[2]) + sum8(v[3])) + sum8(v[4]);
#pragma unroll
                for (int o = 8; o; o >>= 1) sm += __shfl_xor_sync(0xffffffffu, sm, o);
                if ((lane & 15) == 0 && t128 < 80) st_tag(&S->wsum[j * 160 + g * 5 + wr], sm, epoch);
            }
            const int row = t128 >> 1, hf = t128 & 1;
            const uint32_t base = sR + row * 128, sw = (hf * 4) ^ (row & 7);
            float sm[2] = {0.f, 0.f}, sq[2] = {0.f, 0.f};
            uint4 va[4];
            mbar_wait_hot(bars + 8 * B_XFULL, 0);
            va[0] = lds128(base + (sw << 4)); va[1] = lds128(base + ((1 ^ sw) << 4));
            auto acc8 = [&](const uint4& p, const uint4& q) {
                const uint32_t vv[8] = {p.x, p.y, p.z, p.w, q.x, q.y, q.z, q.w};
#pragma unroll
                for (int i = 0; i < 8; i++) {
                    const float d0 = bf_lo(vv[i]), d1 = bf_hi(vv[i]);
                    sm[0] += d0; sq[0] = fmaf(d0, d0, sq[0]); sm[1] += d1; sq[1] = fmaf(d1, d1, sq[1]);
                }
            };
#pragma unroll 1
            for (int c = 0; c < 10; c++) {
                va[2] = lds128(base + c * 8192 + ((2 ^ sw) << 4)); va[3] = lds128(base + c * 8192 + ((3 ^ sw) << 4));
                acc8(va[0], va[1]);
                if (c < 9) {
                    mbar_wait_hot(bars + 8 * (B_XFULL + c + 1), 0);
                    va[0] = lds128(base + (c + 1) * 8192 + (sw << 4)); va[1] = lds128(base + (c + 1) * 8192 + ((1 ^ sw) << 4));
                }
                acc8(va[2], va[3]);
            }
            TSTAMP0(21);
            float s0 = sm[0] + sm[1], q0 = sq[0] + sq[1];
            s0 += __shfl_xor_sync(0xffffffffu, s0, 1); q0 += __shfl_xor_sync(0xffffffffu, q0, 1);
            s0 *= (1.0f / 640.0f);
            sts32(sCS + hf * 256 + row * 4, __float_as_uint(hf ? rsqrtf(fmaxf(q0 * (1.0f / 640.0f) - s0 * s0, 0.f) + 1e-5f) : s0));
            bar_arrive(BAR_STAT, 256);
            TSTAMP0(20);
            bar_sync(BAR_TO1, 256);
        }
        float acc[80];
        {
            auto g1 = [&](int i, int s) {
                constexpr uint64_t bA = DH_SW128_K | (dR >> 4), bB = DH_SW128_K | (dB >> 4);
                wgmma_n160<0>(acc, bA + i * 512, bB + s * (BSLOT >> 4), i > 0);
                wgmma_n160<0>(acc, bA + i * 512 + 2, bB + s * (BSLOT >> 4) + 2, 1);
                wgmma_n160<0>(acc, bA + i * 512 + 4, bB + s * (BSLOT >> 4) + 4, 1);
                wgmma_n160<0>(acc, bA + i * 512 + 6, bB + s * (BSLOT >> 4) + 6, 1);
            };
            {
                uint32_t s = wg * (I_G1B % NB), fb = bars + 8 * (wg ? B_FULL + I_G1B % NB : B_XFULL), prev = 0;
                const uint32_t m1 = rel.two ? (wg ? 0x1Eu : 0x3FEu) : 0u, m2 = lead && wg ? 0x1E0u : 0u;
                mbar_wait_hot(fb, 0);
#pragma unroll 1
                for (int i = 0; i < 10; i++) {
                    const uint32_t cur = s, ph = wg && i >= NB - 1;
                    fb += 8;
                    if (++s == NB) { s = 0; fb -= wg * 8 * NB; }
                    const bool ok = mbar_test(fb, ph) || i == 9;
                    wg_fence();
                    g1(i, cur);
                    wg_commit();
                    if (i == 8 && wg) bar_arrive(BAR_TO0, 256);
                    wg_wait<1>();
                    mbar_arrive_if(bars + 8 * (B_EMPTY + prev), (m1 >> i) & 1);
                    mbar_arrive_if(bars + 8 * (B_EMPTY2 + i - 5), (m2 >> i) & 1);
                    prev = cur;
                    mbar_wait_hot(fb, ph, ok);
                }
                if (wg) { wg_wait<0>(); mbar_arrive_if(bars + 8 * (B_EMPTY2 + 4), lead); }
            }
            TSTAMP0(36 + wg);
            if (wg == 0) bar_sync(BAR_STAT, 256);
            mbar_wait_hot(bars + 8 * (B_CRDY + wg), 0);
            const uint32_t rowa = sCS + (16 * w + (lane >> 2)) * 4;
            float s_lo = lds32f(rowa + 256), s_hi = lds32f(rowa + 256 + 32);
            if (wg) { s_lo = -s_lo; s_hi = -s_hi; }
            const float m_lo = -s_lo * lds32f(rowa), m_hi = -s_hi * lds32f(rowa + 32);
            const uint32_t ca = sCS + 512 + (wg * 160 + 2 * (lane & 3)) * 4;
            uint8_t* dst = S->ab + (size_t)(j * 64 + wg * 32 + g) * 20480 + w * 5120 + lane * 4;
            float cl[40], ch[20];
            float2 cc[10];
#pragma unroll
            for (int t = 0; t < 20; t++) {
                const float2 c2 = lds64f(ca + t * 32);
                cl[2 * t] = m_lo * c2.x; cl[2 * t + 1] = m_lo * c2.y;
                if (t < 10) { ch[2 * t] = m_hi * c2.x; ch[2 * t + 1] = m_hi * c2.y; } else cc[t - 10] = c2;
            }
            fence_regs(cl); fence_regs(ch);
            wg_wait<0>();
            release(rel, I_G1A + 9, !wg);
            fence_regs(acc);
            TSTAMP0(5 + 17 * wg);
            if (wg) bar_sync(BAR_WG1, 128);
            const uint32_t sa = sB + 2 * BSLOT + (2 * w + ((lane >> 3) & 1)) * 2560 + (lane >> 4) * 128 + (lane & 7) * 16;
#pragma unroll
            for (int t4 = 0; t4 < 20; t4 += 4) {
                uint32_t o[8];
#pragma unroll
                for (int t = t4; t < t4 + 4; t++) {
                    o[2 * (t - t4)] = pack_bf16(fmaf(acc[4 * t], s_lo, cl[2 * t]), fmaf(acc[4 * t + 1], s_lo, cl[2 * t + 1]));
                    o[2 * (t - t4) + 1] = pack_bf16(fmaf(acc[4 * t + 2], s_hi, t < 10 ? ch[2 * t] : m_hi * cc[t - 10].x),
                                                    fmaf(acc[4 * t + 3], s_hi, t < 10 ? ch[2 * t + 1] : m_hi * cc[t - 10].y));
                }
                if (wg == 0) {
#pragma unroll
                    for (int t = 0; t < 4; t++) { stg32(dst + (t4 + t) * 128, o[2 * t]); stg32(dst + 2560 + (t4 + t) * 128, o[2 * t + 1]); }
                } else {
#pragma unroll
                    for (int t = 0; t < 4; t += 2) {
                        stsm4(sa + (t4 + t) * 128, o[2 * t], o[2 * t + 1], o[2 * t + 2], o[2 * t + 3]);
                        stsm4(sa + 3 * BSLOT + (t4 + t) * 128, o[2 * t], o[2 * t + 1], o[2 * t + 2], o[2 * t + 3]);
                    }
                }
                if (t4 < 12) {
                    const float c = __uint_as_float(clk32());
                    s_lo = link(c, zero, s_lo); s_hi = link(c, zero, s_hi);
                }
            }
            if (wg) fence_async_smem(); else bar_arrive(BAR_TO1, 256);
            warp_arrive(bars + 8 * (B_PUB + wg), lane);
            TSTAMP0(6 + 17 * wg);
        }
        if (wg == 0) {
            {
                const uint32_t ra = sR + ((5 * j) >> 1) * 8192 + (16 * w + ((lane >> 3) & 1) * 8 + (lane & 7)) * 128;
                const uint32_t o4 = (j & 1) * 4, xx = o4 ^ (lane >> 4) ^ (lane & 7);
#pragma unroll
                for (int t = 0; t < 20; t += 2) {
                    uint32_t r0, r1, r2, r3;
                    ldsm4(ra + (((t & 6) ^ xx) << 4) + ((t & 4) ? o4 * 2048 : 0) + (t >> 3) * 8192, r0, r1, r2, r3);
                    acc[4 * t] = bf_lo(r0); acc[4 * t + 1] = bf_hi(r0); acc[4 * t + 2] = bf_lo(r1); acc[4 * t + 3] = bf_hi(r1);
                    acc[4 * t + 4] = bf_lo(r2); acc[4 * t + 5] = bf_hi(r2); acc[4 * t + 6] = bf_lo(r3); acc[4 * t + 7] = bf_hi(r3);
                }
                fence_regs(acc);
                bar_sync(BAR_WG0 + (__float_as_uint(acc[79]) & zero), 128);
                mbar_arrive_if(bars + 8 * (B_EMPTY2 + min(t128, 4)), t128 < 5);
            }
            bar_sync(BAR_TO0, 256);
            TSTAMP0(7);
        }
        uint4 px[10];
        {
            const uint32_t a0 = (uint32_t)(DH_SW128_K | (dR >> 4)) + wg * 512;
            asm volatile("barrier.cluster.wait.acquire.aligned;" ::: "memory");
            mbar_wait_hot(bars + 8 * (B_FULL2 + 1), 0);
#pragma unroll 1
            for (int lap = 0; lap < 7 - wg; lap++) {
#pragma unroll
                for (int i = 1; i <= 5; i++) {
                    if (i == 5 && lap == 6) break;
                    if (i == 2) mbar_wait_hot(bars + 8 * (B_PUB + 1), 0, lap);
                    if (G2_PRIO && i == 6 - G2_PRIO && lap == 5 && !wg) bar_sync(BAR_STAT, 256);
                    if (G2_PRIO && i == 5 && lap == 5 && wg) bar_arrive(BAR_STAT, 256);
                    const uint32_t nf = bars + 8 * (B_FULL2 + (i + 1) % 5), np = (lap + (i >= 4)) & 1;
                    const bool ok = mbar_test(nf, np) || (i == 4 && lap == 6) || (i == 5 && lap == 5 && wg);
                    wg_fence();
#pragma unroll
                    for (int q = 0; q < 4; q++)
                        wgmma_n160<1>(acc, (DH_SW128_K >> 32 << 32) | (a0 + (i % 5) * 1024 + 2 * q),
                                      (DH_BLK_B | (dB >> 4)) + (i % 5) * (BSLOT >> 4) + 320 * q, i + q > 1 ? 1 : lap | (wg ^ 1));
                    wg_commit();
                    wg_wait<1>();
                    mbar_arrive_cluster_if((lap == 6 && i > 1 ? rel.dual + 8 * B_EMPTY : bars + 8 * B_EMPTY2) + 8 * (i - 1), lap == 6 && i > 1 ? rel.two : lead && (i > 1 || lap));
                    mbar_wait_hot(nf, np, ok);
                }
            }
            mbar_wait_hot(bars + 8 * B_RXFULL, 0, wg);
#pragma unroll
            for (int t = 0; t < 10; t++) px[t] = lds128(sB + 5 * BSLOT + t128 * 16 + t * 2048);
            wg_wait<0>();
            mbar_arrive_cluster_if(wg ? bars + 8 * B_EMPTY2 : rel.dual + 8 * (B_EMPTY + 4), wg ? lead : rel.two);
            fence_regs(acc);
        }
        if (wg) {
            mbar_wait_hot(bars + 8 * B_RXFREE, 0);
            const uint32_t ra = (sB + 5 * BSLOT + t128 * 16) ^ 0x1000000u, rbar = (bars + 8 * B_RXFULL) ^ 0x1000000u;
#pragma unroll
            for (int t = 0; t < 10; t++)
                asm volatile("st.async.weak.shared::cluster.mbarrier::complete_tx::bytes.v4.b32 [%0], {%1,%2,%3,%4}, [%5];"
                    :: "r"(ra + t * 2048), "r"(pack_bf16(acc[8 * t], acc[8 * t + 1])), "r"(pack_bf16(acc[8 * t + 2], acc[8 * t + 3])),
                       "r"(pack_bf16(acc[8 * t + 4], acc[8 * t + 5])), "r"(pack_bf16(acc[8 * t + 6], acc[8 * t + 7])), "r"(rbar) : "memory");
            TSTAMP0(30);
        } else {
            TSTAMP0(8); CSTAMP0(14);
            const uint32_t sa = sR + (lane >> 4) * 1024 + (2 * w + ((lane >> 3) & 1)) * 128 + (lane & 7) * 16;
            uint8_t* hd = S->h + (size_t)g * 81920 + j * 20480 + w * 256 + lane * 4;
            uint32_t hq[40];
            float one = 1.0f;
#pragma unroll
            for (int t = 0; t < 10; t++) {
                const uint32_t v[4] = {px[t].x, px[t].y, px[t].z, px[t].w};
#pragma unroll
                for (int i = 0; i < 4; i++) {
                    hq[4 * t + i] = pack_bf16(fmaf(acc[8 * t + 2 * i], one, bf_lo(v[i])), fmaf(acc[8 * t + 2 * i + 1], one, bf_hi(v[i])));
                    stg32(hd + (2 * t + (i >> 1)) * 1024 + (i & 1) * 128, hq[4 * t + i]);
                }
                if (t == 1 || t == 3 || t == 5) one = link(__uint_as_float(clk32()), zero, one);
            }
            warp_arrive(bars + 8 * (B_PUB + PUB_H), lane);
            TSTAMP0(9);
            bar_sync(BAR_WG0, 128);
            if (H_DELAY) spin_until(clk32() + H_DELAY);
            release(rel, 19); release(rel, 20);
#pragma unroll
            for (int t = 0; t < 10; t++) stsm4(sa + t * 2048, hq[4 * t], hq[4 * t + 1], hq[4 * t + 2], hq[4 * t + 3]);
            fence_async_smem();
            warp_arrive(bars + 8 * B_HOWN, lane);
        }
        RowStat st;
        uint8_t* const actp = S->act + (size_t)g * 216 * 1024 + w * 256 + lane * 4;
#pragma unroll 1
        for (int pass = 0; pass <= wg; pass++) {
            float ac[128];
#pragma unroll
            for (int i = 0; i < 128; i++) ac[i] = 0.f;
            fence_regs(ac);
            constexpr uint64_t bA = DH_BLK_A | (dR >> 4), bB = DH_W32 | (dB >> 4);
            auto m256 = [&](uint32_t a, int s, int accumulate) {
                wgmma_n256<1>(ac, (bA >> 32 << 32) | (uint32_t)((uint32_t)bA + a), bB + s * (BSLOT >> 4), accumulate);
                wgmma_n256<1>(ac, (bA >> 32 << 32) | (uint32_t)((uint32_t)bA + a + 128), bB + s * (BSLOT >> 4) + 128, 1);
            };
            auto mq = [&](int i, int s) { m256(i * 256, s, i > 0); };
            auto mr = [&](int lap, int i, int s) { m256((5 + lap * NB + i) * 256, s, 1); };
            if (pass == 0) {
                if (wg) {
                    mbar_wait_hot(bars + 8 * B_HOWN, 0);
                    TSTAMP0(26);
                    consume<I_S1Q, 5>(rel, BAR_TO0, mq);
                    bar_sync(BAR_TO1, 256);
                    TSTAMP0(27);
                    consume_laps<I_S1R, 15>(rel, BAR_TO0, mr);
                } else {
                    bar_sync(BAR_TO0, 256);
                    consume<I_S2Q, 5>(rel, BAR_TO1, mq);
                    TSTAMP0(10);
                    {
                        const uint32_t base = sR + (16 * w + (lane & 15)) * 16;
                        const float piv = bf_lo(__float_as_uint(lds32f(base)));
                        float s0 = 0.f, s1 = 0.f, q0 = 0.f, q1 = 0.f;
#pragma unroll 2
                        for (int u = 0; u < 10; u++) {
                            const uint4 v = lds128(base + ((lane >> 4) * 10 + u) * 1024);
                            const uint32_t vv[4] = {v.x, v.y, v.z, v.w};
#pragma unroll
                            for (int i = 0; i < 4; i++) {
                                const float d0 = bf_lo(vv[i]) - piv, d1 = bf_hi(vv[i]) - piv;
                                s0 += d0; q0 = fmaf(d0, d0, q0); s1 += d1; q1 = fmaf(d1, d1, q1);
                            }
                        }
                        s0 += s1; q0 += q1;
                        s0 += __shfl_xor_sync(0xffffffffu, s0, 16); q0 += __shfl_xor_sync(0xffffffffu, q0, 16);
                        const float md = s0 * (1.0f / 160.0f);
                        st_tag((uint2*)&S->stats[(g * 4 + j) * 64 + 16 * w + (lane & 15)] + (lane >> 4), (lane >> 4) ? fmaxf(q0 - s0 * md, 0.f) : piv + md, epoch);
                    }
                    TSTAMP0(17);
                    bar_sync(BAR_TO0, 256);
                    consume_laps<I_S2R, 15>(rel, BAR_TO1, mr);
                }
            } else {
                bar_sync(BAR_TO1, 256);
                consume_laps<I_S3, 20>(rel, BAR_TO0, [&](int lap, int i, int s) { m256((lap * NB + i) * 256, s, i ? 1 : lap); });
            }
            fence_regs(ac);
            TSTAMP0((wg ? 28 : 12) + 3 * pass);
            mbar_wait_hot(bars + 8 * B_STAT2, 0);
            {
                const uint32_t ra = sR + OFF_ST2 + (16 * w + (lane >> 2)) * 4;
                const float c0 = TANHV ? 0.7978845608028654f : -2.0f * 0.7978845608028654f * 1.4426950408889634f, c1 = c0 * 0.044715f;
#pragma unroll
                for (int h = 0; h < 2; h++) {
                    const float iv = lds32f(ra + 256 + 32 * h), rs = rsqrtf(iv);
                    st.nm[h] = -lds32f(ra + 32 * h); st.iv[h] = TANHV ? 0.5f * rs * rs : iv; st.k1[h] = c0 * rs; st.k2[h] = c1 * rs * rs * rs;
                }
            }
            const int sub = 2 * pass + 1 - wg;
            g3_epilogue<16>(ac, st, sCS + sub * 1024 + (lane & 3) * 16, actp + (48 * j + 16 * sub) * 1024, zero);
            warp_arrive(bars + 8 * (B_PUB + PUB_S1 + sub), lane);
            TSTAMP0((wg ? 29 : 13) + 3 * pass);
        }
        if (wg == 0) {
            float a4[64];
            bar_sync(BAR_TO0, 256);
            consume<I_S4, 8>(rel, BAR_TO1, [&](int i, int s) {
                constexpr uint64_t bA = DH_BLK_A | (dR >> 4), bB = DH_W80 | (dB >> 4);
#pragma unroll
                for (int q = 0; q < 5; q++) wgmma_n128<1>(a4, bA + ((i + 2) & 7) * 640 + q * 128, bB + s * (BSLOT >> 4) + q * 128, i + q > 0);
            });
            fence_regs(a4);
            TSTAMP0(15);
            if (j < 3) g3_epilogue<8>(a4, st, sCS + 3072 + (lane & 3) * 16, actp + (192 + 8 * j) * 1024, zero);
            warp_arrive(bars + 8 * (B_PUB + PUB_S1 + 3), lane);
            TSTAMP0(16);
        } else {
            float a0[64], a1[16];
            const int rot = (j & 1) * 4;
            bar_sync(BAR_TO1, 256);
            consume_laps<I_G4, 27, false>(rel, -1, [&](int lap, int i, int s) {
                constexpr uint64_t bA = DH_BLK_A | ((dR + 3 * 8192) >> 4), bB = DH_W64 | (dB >> 4), bH = DH_BLK_H | ((dB + 16384) >> 4);
#pragma unroll
                for (int q = 0; q < 4; q++) {
                    wgmma_n128<1>(a0, bA + i * 512 + q * 128, bB + s * (BSLOT >> 4) + q * 128, i + q ? 1 : lap);
                    wgmma_n32<1>(a1, bA + i * 512 + q * 128, bH + s * (BSLOT >> 4) + q * 64, i + q ? 1 : lap);
                }
            });
            uint32_t hp[40];
            {
                const uint32_t ha = sR + (lane >> 4) * 1024 + (2 * w + ((lane >> 3) & 1)) * 128 + (lane & 7) * 16;
                const uint32_t h0 = ha + rot * 1024, h1 = ha - rot * 4096;
#pragma unroll
                for (int t = 0; t < 20; t += 2) ldsm4((t < 16 ? h0 : h1) + t * 1024, hp[2 * t], hp[2 * t + 1], hp[2 * t + 2], hp[2 * t + 3]);
            }
            wg_wait<0>();
            fence_regs(a0); fence_regs(a1);
            TSTAMP0(34); CSTAMP0(24);
            static_assert((I_G4 + 26) % NB == 3, "slots 5 and 6 are long idle");
            const uint32_t stg = sB + 5 * BSLOT + w * (16 * 336);
            const uint32_t sa = stg + ((lane & 7) + ((lane >> 3) & 1) * 8) * 336 + (lane >> 4) * 16;
#pragma unroll
            for (int t = 0; t < 20; t += 2) {
                const float* d = t < 16 ? &a0[4 * t] : &a1[4 * (t - 16)];
                stsm4(sa + t * 16, add_bf16x2(pack_bf16(d[0], d[1]), hp[2 * t]), add_bf16x2(pack_bf16(d[2], d[3]), hp[2 * t + 1]),
                      add_bf16x2(pack_bf16(d[4], d[5]), hp[2 * t + 2]), add_bf16x2(pack_bf16(d[6], d[7]), hp[2 * t + 3]));
            }
            __syncwarp();
            __nv_bfloat16* op = P.out + (size_t)(g * 64 + 16 * w) * D_ + j * 160;
            {
                __nv_bfloat16* o0 = op + (lane >> 4) * D_ + rot * 8 + (lane & 15) * 8;
                const uint32_t l0 = stg + (lane >> 4) * 336 + (lane & 15) * 16;
#pragma unroll
                for (int i = 0; i < 8; i++) stg128(o0 + i * 2 * D_, lds128(l0 + i * 2 * 336));
                __nv_bfloat16* o1 = op + (lane >> 2) * D_ + (128 - rot * 32) + (lane & 3) * 8;
                const uint32_t l1 = stg + (lane >> 2) * 336 + 256 + (lane & 3) * 16;
#pragma unroll
                for (int i = 0; i < 2; i++) stg128(o1 + i * 8 * D_, lds128(l1 + i * 8 * 336));
            }
            if (lead) S->epoch[slot] = epoch;
            TSTAMP0(35);
            TDUMP();
        }
    }
}

typedef CUresult (*EncodeFn)(CUtensorMap*, CUtensorMapDataType, cuuint32_t, void*, const cuuint64_t*, const cuuint64_t*,
                             const cuuint32_t*, const cuuint32_t*, CUtensorMapInterleave, CUtensorMapSwizzle,
                             CUtensorMapL2promotion, CUtensorMapFloatOOBfill);

#define L2PROMO CU_TENSOR_MAP_L2_PROMOTION_L2_128B
void make2d(EncodeFn enc, CUtensorMap* m, const void* p, uint64_t d0, uint64_t d1, uint32_t b0, uint32_t b1) {
    cuuint64_t dims[2] = {d0, d1}, strides[1] = {d0 * 2};
    cuuint32_t box[2] = {b0, b1}, es[2] = {1, 1};
    enc(m, CU_TENSOR_MAP_DATA_TYPE_BFLOAT16, 2, const_cast<void*>(p), dims, strides, box, es, CU_TENSOR_MAP_INTERLEAVE_NONE,
        CU_TENSOR_MAP_SWIZZLE_128B, L2PROMO, CU_TENSOR_MAP_FLOAT_OOB_FILL_NONE);
}
void make3d(EncodeFn enc, CUtensorMap* m, const void* p, uint64_t rows, uint64_t cols, uint32_t w, uint32_t br, uint32_t bg) {
    cuuint64_t dims[3] = {w, rows, cols / w}, strides[2] = {cols * 2, w * 2};
    cuuint32_t box[3] = {w, br, bg}, es[3] = {1, 1, 1};
    enc(m, CU_TENSOR_MAP_DATA_TYPE_BFLOAT16, 3, const_cast<void*>(p), dims, strides, box, es, CU_TENSOR_MAP_INTERLEAVE_NONE,
        CU_TENSOR_MAP_SWIZZLE_128B, CU_TENSOR_MAP_L2_PROMOTION_L2_128B, CU_TENSOR_MAP_FLOAT_OOB_FILL_NONE);
}

}

extern "C" void kernel_launch(void* const* d_in, const int* in_sizes, int n_in, void* d_out, int out_size) {
    static EncodeFn enc = nullptr;
    static Scratch* scratch = nullptr;
    if (!enc) {
        void* fn = nullptr;
        cudaDriverEntryPointQueryResult st;
        cudaGetDriverEntryPoint("cuTensorMapEncodeTiled", &fn, cudaEnableDefault, &st);
        enc = (EncodeFn)fn;
        cudaFuncSetAttribute(fused_kernel, cudaFuncAttributeMaxDynamicSharedMemorySize, SMEM_BYTES);
        cudaGetSymbolAddress((void**)&scratch, g_scratch);
    }
    Params P;
    P.s = scratch;
    P.zero = 0;
    P.xp = (const __nv_bfloat16*)d_in[0];
    P.wd_re = (const __nv_bfloat16*)d_in[3];
    P.wd_im = (const __nv_bfloat16*)d_in[4];
    P.w_gate = (const __nv_bfloat16*)d_in[6];
    P.w_up = (const __nv_bfloat16*)d_in[7];
    P.w_down = (const __nv_bfloat16*)d_in[8];
    P.out = (__nv_bfloat16*)d_out;
    make2d(enc, &P.x, d_in[0], D_, S_, 64, 64);
    make2d(enc, &P.wdre, d_in[3], D_, D_, 64, 160);
    make2d(enc, &P.wdim, d_in[4], D_, D_, 64, 160);
    make2d(enc, &P.wsre, d_in[1], S_, S_, 64, 64);
    make2d(enc, &P.wsim, d_in[2], S_, S_, 64, 64);
    make3d(enc, &P.wg, d_in[6], D_, F_, 64, 32, 2);
    make3d(enc, &P.wu, d_in[7], D_, F_, 64, 32, 2);
    make3d(enc, &P.wg1, d_in[6], D_, F_, 64, 80, 1);
    make3d(enc, &P.wu1, d_in[7], D_, F_, 64, 80, 1);
    make3d(enc, &P.wd, d_in[8], F_, D_, 64, 64, 2);
    make3d(enc, &P.wdh, d_in[8], F_, D_, 64, 216, 1);
    cudaLaunchConfig_t cfg = {};
    cfg.gridDim = dim3(132);
    cfg.blockDim = dim3(384);
    cfg.dynamicSmemBytes = SMEM_BYTES;
    cfg.stream = cudaStreamPerThread;
    cudaLaunchAttribute at[1];
    at[0].id = cudaLaunchAttributeCooperative;
    at[0].val.cooperative = 1;
    cfg.attrs = at;
    cfg.numAttrs = 0;
    cudaLaunchKernelEx(&cfg, fused_kernel, P);
}
```
